```python
import torch

def _softmax(x, axis=-1):
    return torch.softmax(x, dim=axis)
def _gelu(x):
    return torch.nn.functional.gelu(x, approximate="tanh")
def _silu(x):
    return torch.nn.functional.silu(x)
def _sigmoid(x):
    return torch.sigmoid(x)
def _layernorm(x, axis=-1, eps=1e-5):
    m = x.mean(dim=axis, keepdim=True)
    v = x.var(dim=axis, keepdim=True, unbiased=False)
    return (x - m) / torch.sqrt(v + eps)
def _scatter_add(tgt, idx, src, axis=0):
    return tgt.clone().index_add_(axis, idx, src)
def _segment_sum(src, seg, n):
    out = torch.zeros((n,) + src.shape[1:], dtype=src.dtype)
    return out.index_add_(0, seg, src)
def _pad(x, pw):
    flat = tuple(v for pair in reversed(pw) for v in pair)
    return torch.nn.functional.pad(x, flat)

kernel_name = 'gated_mix__grouped_kv_mqa__grouped_kv_mqa__prompt'

def setup_inputs():

    _w = (lambda a: (lambda t: t.to(torch.bfloat16) if t.is_floating_point() else t)(torch.as_tensor(a)))
    def _A_setup():
        B, S, D, H = 1, 2048, 512, 32
        Dh = D // H
        return {
            "x": _w((lambda *s: torch.randn(*s, dtype=torch.bfloat16) * 0.05)(B, S, D)),
            "wq": _w((lambda *s: torch.randn(*s, dtype=torch.bfloat16) * 0.8)(D, H * Dh)),
            "wk": _w((lambda *s: torch.randn(*s, dtype=torch.bfloat16) * 0.8)(D, Dh)),
            "wv": _w((lambda *s: torch.randn(*s, dtype=torch.bfloat16) * 0.05)(D, Dh)),
            "wo": _w((lambda *s: torch.randn(*s, dtype=torch.bfloat16) * 0.05)(H * Dh, D)),
        }
    _A_in = _A_setup()

    def _B_setup():
        B, S, D, H = 1, 2048, 512, 32
        Dh = D // H
        return {
            "x": _w((lambda *s: torch.randn(*s, dtype=torch.bfloat16) * 0.05)(B, S, D)),
            "wq": _w((lambda *s: torch.randn(*s, dtype=torch.bfloat16) * 0.8)(D, H * Dh)),
            "wk": _w((lambda *s: torch.randn(*s, dtype=torch.bfloat16) * 0.8)(D, Dh)),
            "wv": _w((lambda *s: torch.randn(*s, dtype=torch.bfloat16) * 0.05)(D, Dh)),
            "wo": _w((lambda *s: torch.randn(*s, dtype=torch.bfloat16) * 0.05)(H * Dh, D)),
        }
    _B_in = _B_setup()

    return {
        "A_x": _A_in["x"],
        "A_wq": _A_in["wq"],
        "A_wk": _A_in["wk"],
        "A_wv": _A_in["wv"],
        "A_wo": _A_in["wo"],
        "B_x": _B_in["x"],
        "B_wq": _B_in["wq"],
        "B_wk": _B_in["wk"],
        "B_wv": _B_in["wv"],
        "B_wo": _B_in["wo"],
        "gate_w": _w((lambda *s: torch.randn(*s, dtype=torch.bfloat16) * 0.05)(512) * 16.0),
    }

def reference(A_x, A_wq, A_wk, A_wv, A_wo, B_x, B_wq, B_wk, B_wv, B_wo, gate_w):
    def _A_ref(x, wq, wk, wv, wo):
        B, S, D = x.shape
        H = 32
        Dh = D // H
        q = (lambda x, *d: x.permute(*d))((x @ wq).reshape(B, S, H, Dh), 0, 2, 1, 3)
        k = x @ wk
        v = x @ wv
        scores = torch.einsum("bhqd,bkd->bhqk", q, k) * (Dh ** -0.5)
        p = _softmax(scores, axis=-1)
        o = torch.einsum("bhqk,bkd->bhqd", p, v)
        return (lambda x, *d: x.permute(*d))(o, 0, 2, 1, 3).reshape(B, S, H * Dh) @ wo

    def _B_ref(x, wq, wk, wv, wo):
        B, S, D = x.shape
        H = 32
        Dh = D // H
        q = (lambda x, *d: x.permute(*d))((x @ wq).reshape(B, S, H, Dh), 0, 2, 1, 3)
        k = x @ wk
        v = x @ wv
        scores = torch.einsum("bhqd,bkd->bhqk", q, k) * (Dh ** -0.5)
        p = _softmax(scores, axis=-1)
        o = torch.einsum("bhqk,bkd->bhqd", p, v)
        return (lambda x, *d: x.permute(*d))(o, 0, 2, 1, 3).reshape(B, S, H * Dh) @ wo

    x = A_x
    g = _sigmoid((x * gate_w).sum(-1, keepdims=True))
    a = _A_ref(x, A_wq, A_wk, A_wv, A_wo)
    b = _B_ref(x, B_wq, B_wk, B_wv, B_wo)
    return g * a + (1 - g) * b
```

```cpp
#include <cuda_runtime.h>
#include <cuda_bf16.h>
#include <cuda.h>
#include <stdint.h>

typedef __nv_bfloat16 bf16;

#define SEQ 2048
#define DM 512
#define ROWS 65536

__device__ __align__(1024) bf16 g_Q[2 * ROWS * 16];
__device__ __align__(1024) bf16 g_KV[2 * 4 * SEQ * 8];
__device__ __align__(1024) bf16 g_O[2 * ROWS * 16];
__device__ float g_gate[SEQ];
__device__ float g_nrm[128];

__device__ __forceinline__ uint32_t smem_u32(const void* p) { return (uint32_t)__cvta_generic_to_shared(p); }
__device__ __forceinline__ uint64_t make_desc(uint32_t saddr, uint32_t lbo, uint32_t sbo, uint32_t swz) {
    uint64_t d = 0;
    d |= (uint64_t)((saddr & 0x3FFFF) >> 4);
    d |= (uint64_t)((lbo & 0x3FFFF) >> 4) << 16;
    d |= (uint64_t)((sbo & 0x3FFFF) >> 4) << 32;
    d |= (uint64_t)swz << 62;
    return d;
}
__device__ __forceinline__ void wg_fence() { asm volatile("wgmma.fence.sync.aligned;" ::: "memory"); }
__device__ __forceinline__ void wg_commit() { asm volatile("wgmma.commit_group.sync.aligned;" ::: "memory"); }
template <int N> __device__ __forceinline__ void wg_wait() { asm volatile("wgmma.wait_group.sync.aligned %0;" ::"n"(N) : "memory"); }
template <int N> __device__ __forceinline__ void fence_regs(float* d) {
#pragma unroll
    for (int i = 0; i < N; i++) asm volatile("" : "+f"(d[i])::"memory");
}
__device__ __forceinline__ void mbar_init(uint32_t bar, uint32_t cnt) { asm volatile("mbarrier.init.shared::cta.b64 [%0], %1;" ::"r"(bar), "r"(cnt)); }
__device__ __forceinline__ void mbar_expect_tx(uint32_t bar, uint32_t bytes) {
    asm volatile("mbarrier.arrive.expect_tx.shared::cta.b64 _, [%0], %1;" ::"r"(bar), "r"(bytes) : "memory");
}
__device__ __forceinline__ void mbar_arrive(uint32_t bar) { asm volatile("mbarrier.arrive.shared::cta.b64 _, [%0];" ::"r"(bar) : "memory"); }
__device__ __forceinline__ void mbar_wait(uint32_t bar, uint32_t parity) {
    asm volatile(
        "{\n.reg .pred p;\n"
        "WAIT_LOOP:\n"
        "mbarrier.try_wait.parity.shared::cta.b64 p, [%0], %1;\n"
        "@p bra DONE;\n"
        "bra WAIT_LOOP;\n"
        "DONE:\n}" ::"r"(bar), "r"(parity) : "memory");
}
__device__ __forceinline__ void bulk_g2s(uint32_t dst, const void* src, uint32_t bytes, uint32_t bar) {
    asm volatile("cp.async.bulk.shared::cluster.global.mbarrier::complete_tx::bytes [%0], [%1], %2, [%3];" ::"r"(dst), "l"(src), "r"(bytes), "r"(bar) : "memory");
}
__device__ __forceinline__ void tma_2d(uint32_t dst, const CUtensorMap* map, int c0, int c1, uint32_t bar) {
    asm volatile("cp.async.bulk.tensor.2d.shared::cluster.global.mbarrier::complete_tx::bytes [%0], [%1, {%3, %4}], [%2];" ::"r"(dst), "l"(map), "r"(bar), "r"(c0), "r"(c1) : "memory");
}
__device__ __forceinline__ void pdl_launch() { asm volatile("griddepcontrol.launch_dependents;" ::: "memory"); }
__device__ __forceinline__ void pdl_wait() { asm volatile("griddepcontrol.wait;" ::: "memory"); }
__device__ __forceinline__ void fence_async() { asm volatile("fence.proxy.async;" ::: "memory"); }
__device__ __forceinline__ uint32_t pack_bf16(float lo, float hi) {
    uint32_t r;
    asm("cvt.rn.bf16x2.f32 %0, %1, %2;" : "=r"(r) : "f"(hi), "f"(lo));
    return r;
}
__device__ __forceinline__ float bf_lo(uint32_t u) { return __uint_as_float(u << 16); }
__device__ __forceinline__ float bf_hi(uint32_t u) { return __uint_as_float(u & 0xFFFF0000u); }
__device__ __forceinline__ float bf_round(float x) { return __bfloat162float(__float2bfloat16_rn(x)); }

#define A8(b) "+f"(d[b + 0]), "+f"(d[b + 1]), "+f"(d[b + 2]), "+f"(d[b + 3]), "+f"(d[b + 4]), "+f"(d[b + 5]), "+f"(d[b + 6]), "+f"(d[b + 7])
#define W8(b) "=f"(d[b + 0]), "=f"(d[b + 1]), "=f"(d[b + 2]), "=f"(d[b + 3]), "=f"(d[b + 4]), "=f"(d[b + 5]), "=f"(d[b + 6]), "=f"(d[b + 7])

__device__ __forceinline__ void mma_n136_ss(float* d, uint64_t ad, uint64_t bd) {
    asm volatile(
        "wgmma.mma_async.sync.aligned.m64n136k16.f32.bf16.bf16 "
        "{%0,%1,%2,%3,%4,%5,%6,%7,%8,%9,%10,%11,%12,%13,%14,%15,%16,%17,%18,%19,%20,%21,%22,%23,%24,%25,%26,%27,%28,%29,%30,%31,"
        "%32,%33,%34,%35,%36,%37,%38,%39,%40,%41,%42,%43,%44,%45,%46,%47,%48,%49,%50,%51,%52,%53,%54,%55,%56,%57,%58,%59,%60,%61,%62,%63,"
        "%64,%65,%66,%67}, %68, %69, 1, 1, 1, 0, 1;"
        : A8(0), A8(8), A8(16), A8(24), A8(32), A8(40), A8(48), A8(56), "+f"(d[64]), "+f"(d[65]), "+f"(d[66]), "+f"(d[67])
        : "l"(ad), "l"(bd));
}
__device__ __forceinline__ void mma_n64_ss(float* d, uint64_t ad, uint64_t bd) {
    asm volatile(
        "wgmma.mma_async.sync.aligned.m64n64k16.f32.bf16.bf16 "
        "{%0,%1,%2,%3,%4,%5,%6,%7,%8,%9,%10,%11,%12,%13,%14,%15,%16,%17,%18,%19,%20,%21,%22,%23,%24,%25,%26,%27,%28,%29,%30,%31}, "
        "%32, %33, 1, 1, 1, 0, 1;"
        : A8(0), A8(8), A8(16), A8(24)
        : "l"(ad), "l"(bd));
}
__device__ __forceinline__ void qk_n64(float* d, const uint32_t* a, uint64_t bd) {
    asm volatile(
        "wgmma.mma_async.sync.aligned.m64n64k16.f32.bf16.bf16 "
        "{%0,%1,%2,%3,%4,%5,%6,%7,%8,%9,%10,%11,%12,%13,%14,%15,%16,%17,%18,%19,%20,%21,%22,%23,%24,%25,%26,%27,%28,%29,%30,%31}, "
        "{%32,%33,%34,%35}, %36, 0, 1, 1, 0;"
        : W8(0), W8(8), W8(16), W8(24)
        : "r"(a[0]), "r"(a[1]), "r"(a[2]), "r"(a[3]), "l"(bd));
}
__device__ __forceinline__ void pv_n24(float* d, const uint32_t* a, uint64_t bd) {
    asm volatile(
        "wgmma.mma_async.sync.aligned.m64n24k16.f32.bf16.bf16 {%0,%1,%2,%3,%4,%5,%6,%7,%8,%9,%10,%11}, {%12,%13,%14,%15}, %16, 1, 1, 1, 1;"
        : A8(0), "+f"(d[8]), "+f"(d[9]), "+f"(d[10]), "+f"(d[11])
        : "r"(a[0]), "r"(a[1]), "r"(a[2]), "r"(a[3]), "l"(bd));
}

struct K1Maps {
    CUtensorMap x;
    CUtensorMap wq[2];
    CUtensorMap wkv[4];
};
#define K1_STAGES 5
#define K1_STAGE_BYTES 40960
#define K1_SMEM (K1_STAGES * K1_STAGE_BYTES + 1024 + 256)

__global__ void __launch_bounds__(288, 1) proj_kernel(const __grid_constant__ K1Maps maps, const bf16* __restrict__ x, const bf16* __restrict__ gate_w) {
    extern __shared__ unsigned char smem_raw[];
    const uint32_t sb = (smem_u32(smem_raw) + 1023) & ~1023u;
    const uint32_t bars = sb + K1_STAGES * K1_STAGE_BYTES;
    unsigned int* s_max = (unsigned int*)(smem_raw + (bars - smem_u32(smem_raw)) + 128);
    const int tid = threadIdx.x, warp = tid >> 5, lane = tid & 31;
    const int mb = blockIdx.x >> 3, nb = blockIdx.x & 7;
    const int br = nb >> 2;
    if (tid == 0) {
        for (int i = 0; i < K1_STAGES; i++) {
            mbar_init(bars + i * 8, 1);
            mbar_init(bars + 64 + i * 8, 8);
        }
        *s_max = 0u;
        asm volatile("fence.mbarrier_init.release.cluster;" ::: "memory");
    }
    __syncthreads();
    pdl_launch();
    if (warp == 8) {
        if (lane == 0) {
            for (int kb = 0; kb < 8; kb++) {
                const int st = kb % K1_STAGES;
                if (kb >= K1_STAGES) mbar_wait(bars + 64 + st * 8, 0);
                const uint32_t s0 = sb + st * K1_STAGE_BYTES, fb = bars + st * 8;
                mbar_expect_tx(fb, K1_STAGE_BYTES);
                tma_2d(s0, &maps.x, kb * 64, mb * 128, fb);
                tma_2d(s0 + 16384, &maps.wq[br], (nb & 3) * 128, kb * 64, fb);
                tma_2d(s0 + 24576, &maps.wq[br], (nb & 3) * 128 + 64, kb * 64, fb);
                tma_2d(s0 + 32768, &maps.wkv[nb >> 1], (nb & 1) * 8, kb * 64, fb);
            }
        }
    } else {
        {
            const uint4* gw = (const uint4*)(gate_w + lane * 16);
            uint4 w0 = __ldg(gw), w1 = __ldg(gw + 1);
            uint32_t wv[8] = {w0.x, w0.y, w0.z, w0.w, w1.x, w1.y, w1.z, w1.w};
#pragma unroll
            for (int rr = 0; rr < 2; rr++) {
                const int row = mb * 128 + nb * 16 + warp * 2 + rr;
                const uint4* xp = (const uint4*)(x + (size_t)row * DM + lane * 16);
                uint4 a0 = __ldg(xp), a1 = __ldg(xp + 1);
                uint32_t xv[8] = {a0.x, a0.y, a0.z, a0.w, a1.x, a1.y, a1.z, a1.w};
                float s = 0.f;
#pragma unroll
                for (int i = 0; i < 8; i++) {
                    s += bf_round(bf_lo(xv[i]) * bf_lo(wv[i]));
                    s += bf_round(bf_hi(xv[i]) * bf_hi(wv[i]));
                }
#pragma unroll
                for (int o = 16; o > 0; o >>= 1) s += __shfl_xor_sync(0xffffffffu, s, o);
                if (lane == 0) {
                    s = bf_round(s);
                    g_gate[row] = bf_round(1.f / (1.f + __expf(-s)));
                }
            }
        }
        const int wg = warp >> 2;
        float acc[68];
#pragma unroll
        for (int i = 0; i < 68; i++) acc[i] = 0.f;
        fence_regs<68>(acc);
#pragma unroll 1
        for (int kb = 0; kb < 8; kb++) {
            const int st = kb % K1_STAGES;
            const uint32_t s0 = sb + st * K1_STAGE_BYTES;
            mbar_wait(bars + st * 8, kb >= K1_STAGES ? 1 : 0);
            const uint64_t ad = make_desc(s0 + wg * 8192, 16, 1024, 1);
            const uint64_t bd = make_desc(s0 + 16384, 8192, 1024, 1);
            wg_fence();
#pragma unroll
            for (int kk = 0; kk < 4; kk++) mma_n136_ss(acc, ad + kk * 2, bd + kk * 128);
            wg_commit();
            wg_wait<0>();
            if (kb < 8 - K1_STAGES && lane == 0) mbar_arrive(bars + 64 + st * 8);
        }
        fence_regs<68>(acc);
        const int r = lane >> 2, c = lane & 3;
        const int row = mb * 128 + wg * 64 + (warp & 3) * 16 + r;
        const float qs = 0.25f * 1.4426950408889634f;
        bf16* qp = g_Q + (size_t)br * ROWS * 16 + (size_t)row * DM + (nb & 3) * 128 + 4 * c;
#pragma unroll
        for (int h = 0; h < 8; h++) {
            const float* a = acc + h * 8;
            uint2 v0 = make_uint2(pack_bf16(a[0] * qs, a[1] * qs), pack_bf16(a[4] * qs, a[5] * qs));
            uint2 v1 = make_uint2(pack_bf16(a[2] * qs, a[3] * qs), pack_bf16(a[6] * qs, a[7] * qs));
            *(uint2*)(qp + h * 16) = v0;
            *(uint2*)(qp + 8 * DM + h * 16) = v1;
        }
        const uint32_t k0 = pack_bf16(acc[64], acc[65]), k1 = pack_bf16(acc[66], acc[67]);
        bf16* kvp = g_KV + (size_t)nb * (SEQ * 8) + (size_t)row * 8 + 2 * c;
        *(uint32_t*)kvp = k0;
        *(uint32_t*)(kvp + 64) = k1;
        float m;
        if (((nb >> 1) & 1) == 0) {
            float n0 = bf_lo(k0) * bf_lo(k0) + bf_hi(k0) * bf_hi(k0);
            float n1 = bf_lo(k1) * bf_lo(k1) + bf_hi(k1) * bf_hi(k1);
            n0 += __shfl_xor_sync(0xffffffffu, n0, 1);
            n1 += __shfl_xor_sync(0xffffffffu, n1, 1);
            n0 += __shfl_xor_sync(0xffffffffu, n0, 2);
            n1 += __shfl_xor_sync(0xffffffffu, n1, 2);
            m = __uint_as_float(max(__float_as_uint(n0), __float_as_uint(n1)));
        } else {
            uint32_t u = max(max((k0 << 16) & 0x7FFFFFFFu, k0 & 0x7FFF0000u), max((k1 << 16) & 0x7FFFFFFFu, k1 & 0x7FFF0000u));
            m = __uint_as_float(u);
        }
        unsigned int mu = __reduce_max_sync(0xffffffffu, __float_as_uint(m));
        if (lane == 0) atomicMax(s_max, mu);
        asm volatile("bar.sync 1, 256;" ::: "memory");
        if (tid == 0) g_nrm[blockIdx.x] = __uint_as_float(*s_max);
    }
}

__device__ __forceinline__ float ex2(float x) {
    float e;
    asm("ex2.approx.ftz.f32 %0, %1;" : "=f"(e) : "f"(x));
    return e;
}
__device__ __forceinline__ uint32_t exp_pair_mufu(float x0, float x1) { return pack_bf16(ex2(x0), ex2(x1)); }

#define MAGIC0 (98304.0f + 127.0f - 75.0f / 128.0f)
#define MAGIC1 (98304.0f + 127.0f - 75.0f / 128.0f - 143.5f)
template <int PRM>
__device__ __forceinline__ uint32_t exp_pair_poly(float x0, float x1, uint32_t c3f) {
    float t0 = x0 + MAGIC0;
    float t1 = x1 + (PRM ? MAGIC0 : MAGIC1);
    uint32_t L, y2, E, r;
    if (PRM)
        asm("prmt.b32 %0, %1, %2, 0x5410;" : "=r"(L) : "r"(__float_as_uint(t0)), "r"(__float_as_uint(t1)));
    else
        L = __float_as_uint(t1) * 65536u + __float_as_uint(t0);
    asm("lop3.b32 %0, %1, 0x007F007F, %2, 0xEA;" : "=r"(y2) : "r"(L), "r"(c3f));
    E = L & 0x7F807F80u;
    asm("fma.rn.bf16x2 %0, %1, %2, %3;" : "=r"(r) : "r"(L), "r"(y2), "r"(E));
    return r;
}
#define EXP_MASK 0x4949u
template <int BASE>
__device__ __forceinline__ void exp_half(const float* s, uint32_t* p, uint32_t c3f) {
#pragma unroll
    for (int i = 0; i < 8; i++) {
        if ((EXP_MASK >> (BASE + i)) & 1) p[i] = exp_pair_mufu(s[2 * i], s[2 * i + 1]);
        else if (i & 1) p[i] = exp_pair_poly<1>(s[2 * i], s[2 * i + 1], c3f);
        else p[i] = exp_pair_poly<0>(s[2 * i], s[2 * i + 1], c3f);
    }
}

#define SM_K 0
#define SM_V 65536
#define SM_ONES 131072
#define SM_BAR 163840
#define K2_SMEM (163840 + 128 + 1024)

__device__ __forceinline__ void attn_tile_slow(const uint32_t* q, uint64_t kd0, uint64_t vd0, float* oo) {
    float s[32], o[12];
    uint32_t p[16];
    uint32_t qq[4] = {q[0], q[1], q[2], q[3]};
    float m0 = -INFINITY, m1 = -INFINITY;
#pragma unroll 1
    for (int ch = 0; ch < 32; ch++) {
        wg_fence();
        qk_n64(s, qq, kd0 + (uint64_t)(ch * 64));
        wg_commit();
        wg_wait<0>();
        fence_regs<32>(s);
#pragma unroll
        for (int j = 0; j < 8; j++) {
            m0 = fmaxf(m0, fmaxf(s[4 * j], s[4 * j + 1]));
            m1 = fmaxf(m1, fmaxf(s[4 * j + 2], s[4 * j + 3]));
        }
    }
    m0 = fmaxf(m0, __shfl_xor_sync(0xffffffffu, m0, 1));
    m1 = fmaxf(m1, __shfl_xor_sync(0xffffffffu, m1, 1));
    m0 = fmaxf(m0, __shfl_xor_sync(0xffffffffu, m0, 2));
    m1 = fmaxf(m1, __shfl_xor_sync(0xffffffffu, m1, 2));
#pragma unroll
    for (int i = 0; i < 12; i++) o[i] = 0.f;
    fence_regs<12>(o);
#pragma unroll 1
    for (int ch = 0; ch < 32; ch++) {
        wg_fence();
        qk_n64(s, qq, kd0 + (uint64_t)(ch * 64));
        wg_commit();
        wg_wait<0>();
        fence_regs<32>(s);
#pragma unroll
        for (int j = 0; j < 8; j++) {
            p[2 * j] = exp_pair_mufu(s[4 * j] - m0, s[4 * j + 1] - m0);
            p[2 * j + 1] = exp_pair_mufu(s[4 * j + 2] - m1, s[4 * j + 3] - m1);
        }
        wg_fence();
#pragma unroll
        for (int j = 0; j < 4; j++) pv_n24(o, p + 4 * j, vd0 + (uint64_t)(ch * 64 + 16 * j));
        wg_commit();
        wg_wait<0>();
        fence_regs<12>(o);
    }
#pragma unroll
    for (int i = 0; i < 12; i++) oo[i] = o[i];
}

__global__ void __launch_bounds__(512, 1) attn_kernel() {
    extern __shared__ unsigned char smem_raw[];
    const uint32_t sb = (smem_u32(smem_raw) + 1023) & ~1023u;
    unsigned char* smem = smem_raw + (sb - smem_u32(smem_raw));
    const int tid = threadIdx.x;
    const int br = blockIdx.x >> 6;
    const int rb = blockIdx.x & 63;
    if (tid == 0) {
        for (int i = 0; i < 8; i++) mbar_init(sb + SM_BAR + i * 8, 1);
        asm volatile("fence.mbarrier_init.release.cluster;" ::: "memory");
    }
#pragma unroll
    for (int i = 0; i < 4; i++) *(uint4*)(smem + SM_ONES + (tid + i * 512) * 16) = make_uint4(0x00003F80u, 0, 0, 0);
    asm volatile("fence.proxy.async.shared::cta;" ::: "memory");
    __syncthreads();
    pdl_launch();
    pdl_wait();
    if (tid == 0) {
        fence_async();
        const unsigned char* src = (const unsigned char*)g_KV + (size_t)br * 131072;
        for (int g = 0; g < 8; g++) {
            const uint32_t bar = sb + SM_BAR + g * 8;
            mbar_expect_tx(bar, 16384);
            for (int pl = 0; pl < 4; pl++) bulk_g2s(sb + pl * 32768 + g * 4096, src + pl * 32768 + g * 4096, 4096, bar);
        }
    }
    const int wg = __shfl_sync(0xffffffffu, tid >> 7, 0), warp = (tid >> 5) & 3, lane = tid & 31;
    const int r = lane >> 2, c = lane & 3;
    float kmax2, vmax;
    {
        const unsigned int a = __float_as_uint(g_nrm[(lane & 15) * 8 + br * 4 + (lane >> 4)]);
        const unsigned int b = __float_as_uint(g_nrm[(lane & 15) * 8 + br * 4 + 2 + (lane >> 4)]);
        unsigned int h = a;
#pragma unroll
        for (int o = 8; o > 0; o >>= 1) h = max(h, __shfl_xor_sync(0xffffffffu, h, o));
        kmax2 = __uint_as_float(h) + __uint_as_float(__shfl_xor_sync(0xffffffffu, h, 16));
        vmax = __uint_as_float(__reduce_max_sync(0xffffffffu, b));
    }
    uint32_t c3f = 0x3F003F00u;
    asm volatile("" : "+r"(c3f));
    const uint64_t kd0 = make_desc(sb + SM_K, 32768, 128, 0);
    const uint64_t vd0 = make_desc(sb + SM_V, 128, 32768, 0);

#pragma unroll 1
    for (int t = 0; t < 4; t++) {
        const int row0 = rb * 1024 + (wg * 4 + t) * 64 + warp * 16;
        const bf16* qp = g_Q + ((size_t)br * ROWS + row0 + r) * 16 + 4 * c;
        uint32_t q[4];
        {
            const uint2 a = *(const uint2*)qp, b = *(const uint2*)(qp + 128);
            q[0] = a.x; q[2] = a.y; q[1] = b.x; q[3] = b.y;
        }
        float n0 = bf_lo(q[0]) * bf_lo(q[0]) + bf_hi(q[0]) * bf_hi(q[0]) + bf_lo(q[2]) * bf_lo(q[2]) + bf_hi(q[2]) * bf_hi(q[2]);
        float n1 = bf_lo(q[1]) * bf_lo(q[1]) + bf_hi(q[1]) * bf_hi(q[1]) + bf_lo(q[3]) * bf_lo(q[3]) + bf_hi(q[3]) * bf_hi(q[3]);
        n0 += __shfl_xor_sync(0xffffffffu, n0, 1);
        n1 += __shfl_xor_sync(0xffffffffu, n1, 1);
        n0 += __shfl_xor_sync(0xffffffffu, n0, 2);
        n1 += __shfl_xor_sync(0xffffffffu, n1, 2);
        const bool unsafe = !(n0 * kmax2 <= 3600.f) || !(n1 * kmax2 <= 3600.f) || !(vmax <= 1.0e15f);
        uint32_t any_unsafe;
        asm volatile(
            "{\n.reg .pred p, q;\nsetp.ne.u32 q, %1, 0;\nbar.red.or.pred p, %2, 128, q;\nselp.u32 %0, 1, 0, p;\n}"
            : "=r"(any_unsafe) : "r"((uint32_t)unsafe), "r"(wg + 1) : "memory");
        float o[12];
        if (any_unsafe) {
            for (int g = 0; g < 8; g++) mbar_wait(sb + SM_BAR + g * 8, 0);
            attn_tile_slow(q, kd0, vd0, o);
        } else {
#pragma unroll
            for (int i = 0; i < 12; i++) o[i] = 0.f;
            fence_regs<12>(o);
            float s0[32], s1[32];
            uint32_t p[16];
            mbar_wait(sb + SM_BAR, 0);
            wg_fence();
            qk_n64(s0, q, kd0);
            wg_commit();
            wg_wait<0>();
            fence_regs<32>(s0);
            uint64_t kd = kd0, vd = vd0;
#pragma unroll 1
            for (uint32_t it = 0; it < 16; it++) {
                wg_fence();
                qk_n64(s1, q, kd + 64);
                wg_commit();
                exp_half<0>(s0, p, c3f);
                wg_fence();
                pv_n24(o, p, vd);
                pv_n24(o, p + 4, vd + 16);
                wg_commit();
                wg_wait<2>();
                exp_half<8>(s0 + 16, p + 8, c3f);
                wg_fence();
                pv_n24(o, p + 8, vd + 32);
                pv_n24(o, p + 12, vd + 48);
                wg_commit();
                wg_wait<1>();
                fence_regs<32>(s1);
                if (it & 1) mbar_wait(sb + SM_BAR + (((it + 1) >> 1) & 7) * 8, 0);
                kd = (it == 15) ? kd0 : kd + 128;
                wg_fence();
                qk_n64(s0, q, kd);
                wg_commit();
                exp_half<0>(s1, p, c3f);
                wg_fence();
                pv_n24(o, p, vd + 64);
                pv_n24(o, p + 4, vd + 80);
                wg_commit();
                wg_wait<2>();
                exp_half<8>(s1 + 16, p + 8, c3f);
                wg_fence();
                pv_n24(o, p + 8, vd + 96);
                pv_n24(o, p + 12, vd + 112);
                wg_commit();
                wg_wait<1>();
                fence_regs<32>(s0);
                vd += 128;
            }
            wg_wait<0>();
            fence_regs<12>(o);
        }
        const float l0 = __shfl_sync(0xffffffffu, o[8], lane & ~3);
        const float l1 = __shfl_sync(0xffffffffu, o[10], lane & ~3);
        const float i0 = 1.f / l0, i1 = 1.f / l1;
        bf16* op = g_O + ((size_t)br * ROWS + row0 + r) * 16 + 2 * c;
        *(uint32_t*)(op) = pack_bf16(o[0] * i0, o[1] * i0);
        *(uint32_t*)(op + 128) = pack_bf16(o[2] * i1, o[3] * i1);
        *(uint32_t*)(op + 8) = pack_bf16(o[4] * i0, o[5] * i0);
        *(uint32_t*)(op + 136) = pack_bf16(o[6] * i1, o[7] * i1);
    }
}

struct K3Maps {
    CUtensorMap o;
    CUtensorMap wo[2];
};
#define K3_STAGES 8
#define K3_STAGE_BYTES 24576
#define K3_SMEM (K3_STAGES * K3_STAGE_BYTES + 1024 + 256)

__global__ void __launch_bounds__(288, 1) out_kernel(const __grid_constant__ K3Maps maps, bf16* __restrict__ out) {
    extern __shared__ unsigned char smem_raw[];
    const uint32_t sb = (smem_u32(smem_raw) + 1023) & ~1023u;
    const uint32_t bars = sb + K3_STAGES * K3_STAGE_BYTES;
    const int tid = threadIdx.x, warp = tid >> 5, lane = tid & 31;
    const int mb = blockIdx.x >> 3, nb = blockIdx.x & 7;
    if (tid == 0) {
        for (int i = 0; i < K3_STAGES; i++) {
            mbar_init(bars + i * 8, 1);
            mbar_init(bars + 64 + i * 8, 8);
        }
        asm volatile("fence.mbarrier_init.release.cluster;" ::: "memory");
    }
    __syncthreads();
    if (warp == 8) {
        if (lane == 0) {
            for (int kb = 0; kb < 8; kb++) {
                mbar_expect_tx(bars + kb * 8, K3_STAGE_BYTES);
                tma_2d(sb + kb * K3_STAGE_BYTES + 16384, &maps.wo[0], nb * 64, kb * 64, bars + kb * 8);
            }
            pdl_wait();
            fence_async();
            for (int kb = 0; kb < 8; kb++) tma_2d(sb + kb * K3_STAGE_BYTES, &maps.o, kb * 64, mb * 128, bars + kb * 8);
            for (int kb = 0; kb < 8; kb++) {
                mbar_wait(bars + 64 + kb * 8, 0);
                mbar_expect_tx(bars + kb * 8, K3_STAGE_BYTES);
                tma_2d(sb + kb * K3_STAGE_BYTES, &maps.o, kb * 64, SEQ + mb * 128, bars + kb * 8);
                tma_2d(sb + kb * K3_STAGE_BYTES + 16384, &maps.wo[1], nb * 64, kb * 64, bars + kb * 8);
            }
        }
    } else {
        const int wg = warp >> 2;
        float aa[32], ab[32];
#pragma unroll
        for (int i = 0; i < 32; i++) { aa[i] = 0.f; ab[i] = 0.f; }
        fence_regs<32>(aa);
        fence_regs<32>(ab);
#pragma unroll 1
        for (int kb = 0; kb < 8; kb++) {
            const uint32_t s0 = sb + kb * K3_STAGE_BYTES;
            mbar_wait(bars + kb * 8, 0);
            const uint64_t ad = make_desc(s0 + wg * 8192, 16, 1024, 1);
            const uint64_t bd = make_desc(s0 + 16384, 8192, 1024, 1);
            wg_fence();
#pragma unroll
            for (int kk = 0; kk < 4; kk++) mma_n64_ss(aa, ad + kk * 2, bd + kk * 128);
            wg_commit();
            wg_wait<0>();
            if (lane == 0) mbar_arrive(bars + 64 + kb * 8);
        }
#pragma unroll 1
        for (int kb = 0; kb < 8; kb++) {
            const uint32_t s0 = sb + kb * K3_STAGE_BYTES;
            mbar_wait(bars + kb * 8, 1);
            const uint64_t ad = make_desc(s0 + wg * 8192, 16, 1024, 1);
            const uint64_t bd = make_desc(s0 + 16384, 8192, 1024, 1);
            wg_fence();
#pragma unroll
            for (int kk = 0; kk < 4; kk++) mma_n64_ss(ab, ad + kk * 2, bd + kk * 128);
            wg_commit();
            wg_wait<0>();
        }
        fence_regs<32>(aa);
        fence_regs<32>(ab);
        const int r = lane >> 2, c = lane & 3;
        const int row = mb * 128 + wg * 64 + (warp & 3) * 16 + r;
        const float g0 = __ldcg(g_gate + row), g1 = __ldcg(g_gate + row + 8);
        const float h0 = bf_round(1.f - g0), h1 = bf_round(1.f - g1);
        bf16* op = out + (size_t)row * DM + nb * 64 + 2 * c;
#pragma unroll
        for (int j = 0; j < 8; j++) {
            const float v0 = bf_round(g0 * bf_round(aa[4 * j])) + bf_round(h0 * bf_round(ab[4 * j]));
            const float v1 = bf_round(g0 * bf_round(aa[4 * j + 1])) + bf_round(h0 * bf_round(ab[4 * j + 1]));
            const float v2 = bf_round(g1 * bf_round(aa[4 * j + 2])) + bf_round(h1 * bf_round(ab[4 * j + 2]));
            const float v3 = bf_round(g1 * bf_round(aa[4 * j + 3])) + bf_round(h1 * bf_round(ab[4 * j + 3]));
            *(uint32_t*)(op + j * 8) = pack_bf16(v0, v1);
            *(uint32_t*)(op + 8 * DM + j * 8) = pack_bf16(v2, v3);
        }
    }
}

typedef CUresult (*EncodeFn)(CUtensorMap*, CUtensorMapDataType, cuuint32_t, void*, const cuuint64_t*, const cuuint64_t*, const cuuint32_t*,
                             const cuuint32_t*, CUtensorMapInterleave, CUtensorMapSwizzle, CUtensorMapL2promotion, CUtensorMapFloatOOBfill);

static void encode_2d(EncodeFn fn, CUtensorMap* m, const void* ptr, uint64_t inner, uint64_t outer, uint32_t box_inner, uint32_t box_outer) {
    cuuint64_t dims[2] = {inner, outer};
    cuuint64_t strides[1] = {inner * 2};
    cuuint32_t box[2] = {box_inner, box_outer};
    cuuint32_t es[2] = {1, 1};
    fn(m, CU_TENSOR_MAP_DATA_TYPE_BFLOAT16, 2, (void*)ptr, dims, strides, box, es, CU_TENSOR_MAP_INTERLEAVE_NONE, CU_TENSOR_MAP_SWIZZLE_128B,
       CU_TENSOR_MAP_L2_PROMOTION_L2_256B, CU_TENSOR_MAP_FLOAT_OOB_FILL_NONE);
}

extern "C" void kernel_launch(void* const* d_in, const int* in_sizes, int n_in, void* d_out, int out_size) {
    (void)in_sizes; (void)n_in; (void)out_size;
    static K1Maps m1;
    static K3Maps m3;
    static const void* cached[11] = {0};
    static bool attr_done = false;
    bool same = true;
    for (int i = 0; i < 11; i++) same = same && (cached[i] == d_in[i]);
    if (!same || !attr_done) {
        void* fnp = nullptr;
        cudaDriverEntryPointQueryResult qr;
        cudaGetDriverEntryPoint("cuTensorMapEncodeTiled", &fnp, cudaEnableDefault, &qr);
        EncodeFn fn = (EncodeFn)fnp;
        void* po = nullptr;
        cudaGetSymbolAddress(&po, g_O);
        encode_2d(fn, &m1.x, d_in[0], DM, SEQ, 64, 128);
        encode_2d(fn, &m1.wq[0], d_in[1], DM, DM, 64, 64);
        encode_2d(fn, &m1.wq[1], d_in[6], DM, DM, 64, 64);
        encode_2d(fn, &m1.wkv[0], d_in[2], 16, DM, 64, 64);
        encode_2d(fn, &m1.wkv[1], d_in[3], 16, DM, 64, 64);
        encode_2d(fn, &m1.wkv[2], d_in[7], 16, DM, 64, 64);
        encode_2d(fn, &m1.wkv[3], d_in[8], 16, DM, 64, 64);
        encode_2d(fn, &m3.o, po, DM, 2 * SEQ, 64, 128);
        encode_2d(fn, &m3.wo[0], d_in[4], DM, DM, 64, 64);
        encode_2d(fn, &m3.wo[1], d_in[9], DM, DM, 64, 64);
        cudaFuncSetAttribute(proj_kernel, cudaFuncAttributeMaxDynamicSharedMemorySize, K1_SMEM);
        cudaFuncSetAttribute(attn_kernel, cudaFuncAttributeMaxDynamicSharedMemorySize, K2_SMEM);
        cudaFuncSetAttribute(out_kernel, cudaFuncAttributeMaxDynamicSharedMemorySize, K3_SMEM);
        for (int i = 0; i < 11; i++) cached[i] = d_in[i];
        attr_done = true;
    }
    cudaStream_t st = cudaStreamPerThread;
    proj_kernel<<<128, 288, K1_SMEM, st>>>(m1, (const bf16*)d_in[0], (const bf16*)d_in[10]);

    cudaLaunchAttribute at[1];
    at[0].id = cudaLaunchAttributeProgrammaticStreamSerialization;
    at[0].val.programmaticStreamSerializationAllowed = 1;
    cudaLaunchConfig_t cfg = {};
    cfg.stream = st;
    cfg.attrs = at;
    cfg.numAttrs = 1;
    cfg.gridDim = dim3(128);
    cfg.blockDim = dim3(512);
    cfg.dynamicSmemBytes = K2_SMEM;
    cudaLaunchKernelEx(&cfg, attn_kernel);
    cfg.blockDim = dim3(288);
    cfg.dynamicSmemBytes = K3_SMEM;
    cudaLaunchKernelEx(&cfg, out_kernel, m3, (bf16*)d_out);
}
```

```cpp
#include <cuda_runtime.h>
#include <cuda_bf16.h>
#include <cuda.h>
#include <stdint.h>

typedef __nv_bfloat16 bf16;

#define SEQ 2048
#define DM 512
#define ROWS 65536

__device__ __align__(1024) bf16 g_Q[2 * ROWS * 16];
__device__ __align__(1024) bf16 g_KV[2 * 4 * SEQ * 8];
__device__ __align__(1024) bf16 g_O[2 * ROWS * 16];
__device__ float g_gate[SEQ];
__device__ float g_nrm[128];

__device__ __forceinline__ uint32_t smem_u32(const void* p) { return (uint32_t)__cvta_generic_to_shared(p); }
__device__ __forceinline__ uint64_t make_desc(uint32_t saddr, uint32_t lbo, uint32_t sbo, uint32_t swz) {
    uint64_t d = 0;
    d |= (uint64_t)((saddr & 0x3FFFF) >> 4);
    d |= (uint64_t)((lbo & 0x3FFFF) >> 4) << 16;
    d |= (uint64_t)((sbo & 0x3FFFF) >> 4) << 32;
    d |= (uint64_t)swz << 62;
    return d;
}
__device__ __forceinline__ void wg_fence() { asm volatile("wgmma.fence.sync.aligned;" ::: "memory"); }
__device__ __forceinline__ void wg_commit() { asm volatile("wgmma.commit_group.sync.aligned;" ::: "memory"); }
template <int N> __device__ __forceinline__ void wg_wait() { asm volatile("wgmma.wait_group.sync.aligned %0;" ::"n"(N) : "memory"); }
template <int N> __device__ __forceinline__ void fence_regs(float* d) {
#pragma unroll
    for (int i = 0; i < N; i++) asm volatile("" : "+f"(d[i])::"memory");
}
__device__ __forceinline__ void mbar_init(uint32_t bar, uint32_t cnt) { asm volatile("mbarrier.init.shared::cta.b64 [%0], %1;" ::"r"(bar), "r"(cnt)); }
__device__ __forceinline__ void mbar_expect_tx(uint32_t bar, uint32_t bytes) {
    asm volatile("mbarrier.arrive.expect_tx.shared::cta.b64 _, [%0], %1;" ::"r"(bar), "r"(bytes) : "memory");
}
__device__ __forceinline__ void mbar_arrive(uint32_t bar) { asm volatile("mbarrier.arrive.shared::cta.b64 _, [%0];" ::"r"(bar) : "memory"); }
__device__ __forceinline__ void mbar_wait(uint32_t bar, uint32_t parity) {
    asm volatile(
        "{\n.reg .pred p;\n"
        "WAIT_LOOP:\n"
        "mbarrier.try_wait.parity.shared::cta.b64 p, [%0], %1;\n"
        "@p bra DONE;\n"
        "bra WAIT_LOOP;\n"
        "DONE:\n}" ::"r"(bar), "r"(parity) : "memory");
}
__device__ __forceinline__ void bulk_g2s(uint32_t dst, const void* src, uint32_t bytes, uint32_t bar) {
    asm volatile("cp.async.bulk.shared::cluster.global.mbarrier::complete_tx::bytes [%0], [%1], %2, [%3];" ::"r"(dst), "l"(src), "r"(bytes), "r"(bar) : "memory");
}
__device__ __forceinline__ void tma_2d(uint32_t dst, const CUtensorMap* map, int c0, int c1, uint32_t bar) {
    asm volatile("cp.async.bulk.tensor.2d.shared::cluster.global.mbarrier::complete_tx::bytes [%0], [%1, {%3, %4}], [%2];" ::"r"(dst), "l"(map), "r"(bar), "r"(c0), "r"(c1) : "memory");
}
__device__ __forceinline__ void pdl_launch() { asm volatile("griddepcontrol.launch_dependents;" ::: "memory"); }
__device__ __forceinline__ void pdl_wait() { asm volatile("griddepcontrol.wait;" ::: "memory"); }
__device__ __forceinline__ void fence_async() { asm volatile("fence.proxy.async;" ::: "memory"); }
__device__ __forceinline__ uint32_t pack_bf16(float lo, float hi) {
    uint32_t r;
    asm("cvt.rn.bf16x2.f32 %0, %1, %2;" : "=r"(r) : "f"(hi), "f"(lo));
    return r;
}
__device__ __forceinline__ float bf_lo(uint32_t u) { return __uint_as_float(u << 16); }
__device__ __forceinline__ float bf_hi(uint32_t u) { return __uint_as_float(u & 0xFFFF0000u); }
__device__ __forceinline__ float bf_round(float x) { return __bfloat162float(__float2bfloat16_rn(x)); }

#define A8(b) "+f"(d[b + 0]), "+f"(d[b + 1]), "+f"(d[b + 2]), "+f"(d[b + 3]), "+f"(d[b + 4]), "+f"(d[b + 5]), "+f"(d[b + 6]), "+f"(d[b + 7])
#define W8(b) "=f"(d[b + 0]), "=f"(d[b + 1]), "=f"(d[b + 2]), "=f"(d[b + 3]), "=f"(d[b + 4]), "=f"(d[b + 5]), "=f"(d[b + 6]), "=f"(d[b + 7])

__device__ __forceinline__ void mma_n136_ss(float* d, uint64_t ad, uint64_t bd) {
    asm volatile(
        "wgmma.mma_async.sync.aligned.m64n136k16.f32.bf16.bf16 "
        "{%0,%1,%2,%3,%4,%5,%6,%7,%8,%9,%10,%11,%12,%13,%14,%15,%16,%17,%18,%19,%20,%21,%22,%23,%24,%25,%26,%27,%28,%29,%30,%31,"
        "%32,%33,%34,%35,%36,%37,%38,%39,%40,%41,%42,%43,%44,%45,%46,%47,%48,%49,%50,%51,%52,%53,%54,%55,%56,%57,%58,%59,%60,%61,%62,%63,"
        "%64,%65,%66,%67}, %68, %69, 1, 1, 1, 0, 1;"
        : A8(0), A8(8), A8(16), A8(24), A8(32), A8(40), A8(48), A8(56), "+f"(d[64]), "+f"(d[65]), "+f"(d[66]), "+f"(d[67])
        : "l"(ad), "l"(bd));
}
__device__ __forceinline__ void mma_n64_ss(float* d, uint64_t ad, uint64_t bd) {
    asm volatile(
        "wgmma.mma_async.sync.aligned.m64n64k16.f32.bf16.bf16 "
        "{%0,%1,%2,%3,%4,%5,%6,%7,%8,%9,%10,%11,%12,%13,%14,%15,%16,%17,%18,%19,%20,%21,%22,%23,%24,%25,%26,%27,%28,%29,%30,%31}, "
        "%32, %33, 1, 1, 1, 0, 1;"
        : A8(0), A8(8), A8(16), A8(24)
        : "l"(ad), "l"(bd));
}
__device__ __forceinline__ void qk_n64(float* d, const uint32_t* a, uint64_t bd) {
    asm volatile(
        "wgmma.mma_async.sync.aligned.m64n64k16.f32.bf16.bf16 "
        "{%0,%1,%2,%3,%4,%5,%6,%7,%8,%9,%10,%11,%12,%13,%14,%15,%16,%17,%18,%19,%20,%21,%22,%23,%24,%25,%26,%27,%28,%29,%30,%31}, "
        "{%32,%33,%34,%35}, %36, 0, 1, 1, 0;"
        : W8(0), W8(8), W8(16), W8(24)
        : "r"(a[0]), "r"(a[1]), "r"(a[2]), "r"(a[3]), "l"(bd));
}
__device__ __forceinline__ void pv_n24(float* d, const uint32_t* a, uint64_t bd) {
    asm volatile(
        "wgmma.mma_async.sync.aligned.m64n24k16.f32.bf16.bf16 {%0,%1,%2,%3,%4,%5,%6,%7,%8,%9,%10,%11}, {%12,%13,%14,%15}, %16, 1, 1, 1, 1;"
        : A8(0), "+f"(d[8]), "+f"(d[9]), "+f"(d[10]), "+f"(d[11])
        : "r"(a[0]), "r"(a[1]), "r"(a[2]), "r"(a[3]), "l"(bd));
}

struct K1Maps {
    CUtensorMap x;
    CUtensorMap wq[2];
    CUtensorMap wkv[4];
};
#define K1_STAGES 5
#define K1_STAGE_BYTES 40960
#define K1_SMEM (K1_STAGES * K1_STAGE_BYTES + 1024 + 256)

__global__ void __launch_bounds__(288, 1) proj_kernel(const __grid_constant__ K1Maps maps, const bf16* __restrict__ x, const bf16* __restrict__ gate_w) {
    extern __shared__ unsigned char smem_raw[];
    const uint32_t sb = (smem_u32(smem_raw) + 1023) & ~1023u;
    const uint32_t bars = sb + K1_STAGES * K1_STAGE_BYTES;
    unsigned int* s_max = (unsigned int*)(smem_raw + (bars - smem_u32(smem_raw)) + 128);
    const int tid = threadIdx.x, warp = tid >> 5, lane = tid & 31;
    const int mb = blockIdx.x >> 3, nb = blockIdx.x & 7;
    const int br = nb >> 2;
    if (tid == 0) {
        for (int i = 0; i < K1_STAGES; i++) {
            mbar_init(bars + i * 8, 1);
            mbar_init(bars + 64 + i * 8, 8);
        }
        *s_max = 0u;
        asm volatile("fence.mbarrier_init.release.cluster;" ::: "memory");
    }
    __syncthreads();
    pdl_launch();
    if (warp == 8) {
        if (lane == 0) {
            for (int kb = 0; kb < 8; kb++) {
                const int st = kb % K1_STAGES;
                if (kb >= K1_STAGES) mbar_wait(bars + 64 + st * 8, 0);
                const uint32_t s0 = sb + st * K1_STAGE_BYTES, fb = bars + st * 8;
                mbar_expect_tx(fb, K1_STAGE_BYTES);
                tma_2d(s0, &maps.x, kb * 64, mb * 128, fb);
                tma_2d(s0 + 16384, &maps.wq[br], (nb & 3) * 128, kb * 64, fb);
                tma_2d(s0 + 24576, &maps.wq[br], (nb & 3) * 128 + 64, kb * 64, fb);
                tma_2d(s0 + 32768, &maps.wkv[nb >> 1], (nb & 1) * 8, kb * 64, fb);
            }
        }
    } else {
        {
            const uint4* gw = (const uint4*)(gate_w + lane * 16);
            uint4 w0 = __ldg(gw), w1 = __ldg(gw + 1);
            uint32_t wv[8] = {w0.x, w0.y, w0.z, w0.w, w1.x, w1.y, w1.z, w1.w};
#pragma unroll
            for (int rr = 0; rr < 2; rr++) {
                const int row = mb * 128 + nb * 16 + warp * 2 + rr;
                const uint4* xp = (const uint4*)(x + (size_t)row * DM + lane * 16);
                uint4 a0 = __ldg(xp), a1 = __ldg(xp + 1);
                uint32_t xv[8] = {a0.x, a0.y, a0.z, a0.w, a1.x, a1.y, a1.z, a1.w};
                float s = 0.f;
#pragma unroll
                for (int i = 0; i < 8; i++) {
                    s += bf_round(bf_lo(xv[i]) * bf_lo(wv[i]));
                    s += bf_round(bf_hi(xv[i]) * bf_hi(wv[i]));
                }
#pragma unroll
                for (int o = 16; o > 0; o >>= 1) s += __shfl_xor_sync(0xffffffffu, s, o);
                if (lane == 0) {
                    s = bf_round(s);
                    g_gate[row] = bf_round(1.f / (1.f + __expf(-s)));
                }
            }
        }
        const int wg = warp >> 2;
        float acc[68];
#pragma unroll
        for (int i = 0; i < 68; i++) acc[i] = 0.f;
        fence_regs<68>(acc);
#pragma unroll 1
        for (int kb = 0; kb < 8; kb++) {
            const int st = kb % K1_STAGES;
            const uint32_t s0 = sb + st * K1_STAGE_BYTES;
            mbar_wait(bars + st * 8, kb >= K1_STAGES ? 1 : 0);
            const uint64_t ad = make_desc(s0 + wg * 8192, 16, 1024, 1);
            const uint64_t bd = make_desc(s0 + 16384, 8192, 1024, 1);
            wg_fence();
#pragma unroll
            for (int kk = 0; kk < 4; kk++) mma_n136_ss(acc, ad + kk * 2, bd + kk * 128);
            wg_commit();
            wg_wait<0>();
            if (kb < 8 - K1_STAGES && lane == 0) mbar_arrive(bars + 64 + st * 8);
        }
        fence_regs<68>(acc);
        const int r = lane >> 2, c = lane & 3;
        const int row = mb * 128 + wg * 64 + (warp & 3) * 16 + r;
        const float qs = 0.25f * 1.4426950408889634f;
        bf16* qp = g_Q + (size_t)br * ROWS * 16 + (size_t)row * DM + (nb & 3) * 128 + 4 * c;
#pragma unroll
        for (int h = 0; h < 8; h++) {
            const float* a = acc + h * 8;
            uint2 v0 = make_uint2(pack_bf16(a[0] * qs, a[1] * qs), pack_bf16(a[4] * qs, a[5] * qs));
            uint2 v1 = make_uint2(pack_bf16(a[2] * qs, a[3] * qs), pack_bf16(a[6] * qs, a[7] * qs));
            *(uint2*)(qp + h * 16) = v0;
            *(uint2*)(qp + 8 * DM + h * 16) = v1;
        }
        const uint32_t k0 = pack_bf16(acc[64], acc[65]), k1 = pack_bf16(acc[66], acc[67]);
        bf16* kvp = g_KV + (size_t)nb * (SEQ * 8) + (size_t)row * 8 + 2 * c;
        *(uint32_t*)kvp = k0;
        *(uint32_t*)(kvp + 64) = k1;
        float m;
        if (((nb >> 1) & 1) == 0) {
            float n0 = bf_lo(k0) * bf_lo(k0) + bf_hi(k0) * bf_hi(k0);
            float n1 = bf_lo(k1) * bf_lo(k1) + bf_hi(k1) * bf_hi(k1);
            n0 += __shfl_xor_sync(0xffffffffu, n0, 1);
            n1 += __shfl_xor_sync(0xffffffffu, n1, 1);
            n0 += __shfl_xor_sync(0xffffffffu, n0, 2);
            n1 += __shfl_xor_sync(0xffffffffu, n1, 2);
            m = __uint_as_float(max(__float_as_uint(n0), __float_as_uint(n1)));
        } else {
            uint32_t u = max(max((k0 << 16) & 0x7FFFFFFFu, k0 & 0x7FFF0000u), max((k1 << 16) & 0x7FFFFFFFu, k1 & 0x7FFF0000u));
            m = __uint_as_float(u);
        }
        unsigned int mu = __reduce_max_sync(0xffffffffu, __float_as_uint(m));
        if (lane == 0) atomicMax(s_max, mu);
        asm volatile("bar.sync 1, 256;" ::: "memory");
        if (tid == 0) g_nrm[blockIdx.x] = __uint_as_float(*s_max);
    }
}

__device__ __forceinline__ float ex2(float x) {
    float e;
    asm("ex2.approx.ftz.f32 %0, %1;" : "=f"(e) : "f"(x));
    return e;
}
__device__ __forceinline__ uint32_t exp_pair_mufu(float x0, float x1) { return pack_bf16(ex2(x0), ex2(x1)); }

#define MAGIC0 (98304.0f + 127.0f - 75.0f / 128.0f)
#define MAGIC1 (98304.0f + 127.0f - 75.0f / 128.0f - 143.5f)
template <int PRM>
__device__ __forceinline__ uint32_t exp_pair_poly(float x0, float x1, uint32_t c3f) {
    float t0 = x0 + MAGIC0;
    float t1 = x1 + (PRM ? MAGIC0 : MAGIC1);
    uint32_t L, y2, E, r;
    if (PRM)
        asm("prmt.b32 %0, %1, %2, 0x5410;" : "=r"(L) : "r"(__float_as_uint(t0)), "r"(__float_as_uint(t1)));
    else
        L = __float_as_uint(t1) * 65536u + __float_as_uint(t0);
    asm("lop3.b32 %0, %1, 0x007F007F, %2, 0xEA;" : "=r"(y2) : "r"(L), "r"(c3f));
    E = L & 0x7F807F80u;
    asm("fma.rn.bf16x2 %0, %1, %2, %3;" : "=r"(r) : "r"(L), "r"(y2), "r"(E));
    return r;
}
#define EXP_MASK 0x4949u
template <int BASE>
__device__ __forceinline__ void exp_half(const float* s, uint32_t* p, uint32_t c3f) {
#pragma unroll
    for (int i = 0; i < 8; i++) {
        if ((EXP_MASK >> (BASE + i)) & 1) p[i] = exp_pair_mufu(s[2 * i], s[2 * i + 1]);
        else if (i & 1) p[i] = exp_pair_poly<1>(s[2 * i], s[2 * i + 1], c3f);
        else p[i] = exp_pair_poly<0>(s[2 * i], s[2 * i + 1], c3f);
    }
}

#define SM_K 0
#define SM_V 65536
#define SM_ONES 131072
#define SM_BAR 163840
#define K2_SMEM (163840 + 128 + 1024)

__device__ __forceinline__ void attn_tile_slow(const uint32_t* qq, uint64_t kd0, uint64_t vd0, float* o, float* s, uint32_t* p) {
    float m0 = -INFINITY, m1 = -INFINITY;
#pragma unroll 1
    for (int ch = 0; ch < 32; ch++) {
        wg_fence();
        qk_n64(s, qq, kd0 + (uint64_t)(ch * 64));
        wg_commit();
        wg_wait<0>();
        fence_regs<32>(s);
#pragma unroll
        for (int j = 0; j < 8; j++) {
            m0 = fmaxf(m0, fmaxf(s[4 * j], s[4 * j + 1]));
            m1 = fmaxf(m1, fmaxf(s[4 * j + 2], s[4 * j + 3]));
        }
    }
    m0 = fmaxf(m0, __shfl_xor_sync(0xffffffffu, m0, 1));
    m1 = fmaxf(m1, __shfl_xor_sync(0xffffffffu, m1, 1));
    m0 = fmaxf(m0, __shfl_xor_sync(0xffffffffu, m0, 2));
    m1 = fmaxf(m1, __shfl_xor_sync(0xffffffffu, m1, 2));
#pragma unroll 1
    for (int ch = 0; ch < 32; ch++) {
        wg_fence();
        qk_n64(s, qq, kd0 + (uint64_t)(ch * 64));
        wg_commit();
        wg_wait<0>();
        fence_regs<32>(s);
#pragma unroll
        for (int j = 0; j < 8; j++) {
            p[2 * j] = exp_pair_mufu(s[4 * j] - m0, s[4 * j + 1] - m0);
            p[2 * j + 1] = exp_pair_mufu(s[4 * j + 2] - m1, s[4 * j + 3] - m1);
        }
        wg_fence();
#pragma unroll
        for (int j = 0; j < 4; j++) pv_n24(o, p + 4 * j, vd0 + (uint64_t)(ch * 64 + 16 * j));
        wg_commit();
        wg_wait<0>();
        fence_regs<12>(o);
    }
}

__global__ void __launch_bounds__(512, 1) attn_kernel() {
    extern __shared__ unsigned char smem_raw[];
    const uint32_t sb = (smem_u32(smem_raw) + 1023) & ~1023u;
    unsigned char* smem = smem_raw + (sb - smem_u32(smem_raw));
    const int tid = threadIdx.x;
    const int br = blockIdx.x >> 6;
    if (tid == 0) {
        for (int i = 0; i < 8; i++) mbar_init(sb + SM_BAR + i * 8, 1);
        asm volatile("fence.mbarrier_init.release.cluster;" ::: "memory");
    }
#pragma unroll
    for (int i = 0; i < 4; i++) *(uint4*)(smem + SM_ONES + (tid + i * 512) * 16) = make_uint4(0x00003F80u, 0, 0, 0);
    asm volatile("fence.proxy.async.shared::cta;" ::: "memory");
    __syncthreads();
    pdl_launch();
    pdl_wait();
    if (tid == 0) {
        fence_async();
        const unsigned char* src = (const unsigned char*)g_KV + (size_t)br * 131072;
        for (int g = 0; g < 8; g++) {
            const uint32_t bar = sb + SM_BAR + g * 8;
            mbar_expect_tx(bar, 16384);
            for (int pl = 0; pl < 4; pl++) bulk_g2s(sb + pl * 32768 + g * 4096, src + pl * 32768 + g * 4096, 4096, bar);
        }
    }
    const int wg = __shfl_sync(0xffffffffu, tid >> 7, 0);
    volatile float* s_kmax2 = (volatile float*)(smem + SM_BAR + 64) + (tid >> 5);
    {
        const int lane = tid & 31;
        const unsigned int a = __float_as_uint(g_nrm[(lane & 15) * 8 + br * 4 + (lane >> 4)]);
        const unsigned int b = __float_as_uint(g_nrm[(lane & 15) * 8 + br * 4 + 2 + (lane >> 4)]);
        unsigned int h = a;
#pragma unroll
        for (int o = 8; o > 0; o >>= 1) h = max(h, __shfl_xor_sync(0xffffffffu, h, o));
        float kmax2 = __uint_as_float(h) + __uint_as_float(__shfl_xor_sync(0xffffffffu, h, 16));
        const float vmax = __uint_as_float(__reduce_max_sync(0xffffffffu, b));
        if (!(vmax <= 1.0e15f)) kmax2 = __uint_as_float(0x7FC00000u);
        if (lane == 0) *s_kmax2 = kmax2;
        __syncwarp();
    }
    uint32_t c3f = 0x3F003F00u;
    asm volatile("" : "+r"(c3f));
    const uint64_t kd0 = make_desc(sb + SM_K, 32768, 128, 0);
    const uint64_t vd0 = make_desc(sb + SM_V, 128, 32768, 0);

#pragma unroll 1
    for (int t = 0; t < 4; t++) {
        uint32_t q[4];
        uint32_t any_unsafe;
        {
            const uint32_t off = (uint32_t)blockIdx.x * 16384u + (uint32_t)(wg * 4 + t) * 1024u + ((tid >> 5) & 3) * 256u + (tid & 31) * 4u;
            const uint2 a = *(const uint2*)(g_Q + off), b = *(const uint2*)(g_Q + off + 128);
            q[0] = a.x; q[2] = a.y; q[1] = b.x; q[3] = b.y;
            float n0 = bf_lo(q[0]) * bf_lo(q[0]) + bf_hi(q[0]) * bf_hi(q[0]) + bf_lo(q[2]) * bf_lo(q[2]) + bf_hi(q[2]) * bf_hi(q[2]);
            float n1 = bf_lo(q[1]) * bf_lo(q[1]) + bf_hi(q[1]) * bf_hi(q[1]) + bf_lo(q[3]) * bf_lo(q[3]) + bf_hi(q[3]) * bf_hi(q[3]);
            n0 += __shfl_xor_sync(0xffffffffu, n0, 1);
            n1 += __shfl_xor_sync(0xffffffffu, n1, 1);
            n0 += __shfl_xor_sync(0xffffffffu, n0, 2);
            n1 += __shfl_xor_sync(0xffffffffu, n1, 2);
            const float kmax2 = *s_kmax2;
            const bool unsafe = !(n0 * kmax2 <= 3600.f) || !(n1 * kmax2 <= 3600.f);
            asm volatile(
                "{\n.reg .pred p, q;\nsetp.ne.u32 q, %1, 0;\nbar.red.or.pred p, %2, 128, q;\nselp.u32 %0, 1, 0, p;\n}"
                : "=r"(any_unsafe) : "r"((uint32_t)unsafe), "r"(wg + 1) : "memory");
        }
        float o[12];
        float s0[32], s1[32];
        uint32_t p[16];
#pragma unroll
        for (int i = 0; i < 12; i++) o[i] = 0.f;
        fence_regs<12>(o);
        if (any_unsafe) {
            for (int g = 0; g < 8; g++) mbar_wait(sb + SM_BAR + g * 8, 0);
            attn_tile_slow(q, kd0, vd0, o, s0, p);
        } else {
            mbar_wait(sb + SM_BAR, 0);
            wg_fence();
            qk_n64(s0, q, kd0);
            wg_commit();
            wg_wait<0>();
            fence_regs<32>(s0);
            uint64_t kd = kd0, vd = vd0;
#pragma unroll 1
            for (uint32_t it = 0; it < 16; it++) {
                wg_fence();
                qk_n64(s1, q, kd + 64);
                wg_commit();
                exp_half<0>(s0, p, c3f);
                wg_fence();
                pv_n24(o, p, vd);
                pv_n24(o, p + 4, vd + 16);
                wg_commit();
                wg_wait<2>();
                exp_half<8>(s0 + 16, p + 8, c3f);
                wg_fence();
                pv_n24(o, p + 8, vd + 32);
                pv_n24(o, p + 12, vd + 48);
                wg_commit();
                wg_wait<1>();
                fence_regs<32>(s1);
                if (it & 1) mbar_wait(sb + SM_BAR + (((it + 1) >> 1) & 7) * 8, 0);
                kd = (it == 15) ? kd0 : kd + 128;
                wg_fence();
                qk_n64(s0, q, kd);
                wg_commit();
                exp_half<0>(s1, p, c3f);
                wg_fence();
                pv_n24(o, p, vd + 64);
                pv_n24(o, p + 4, vd + 80);
                wg_commit();
                wg_wait<2>();
                exp_half<8>(s1 + 16, p + 8, c3f);
                wg_fence();
                pv_n24(o, p + 8, vd + 96);
                pv_n24(o, p + 12, vd + 112);
                wg_commit();
                wg_wait<1>();
                fence_regs<32>(s0);
                vd += 128;
            }
            wg_wait<0>();
            fence_regs<12>(o);
        }
        {
            int tid2;
            asm volatile("mov.u32 %0, %%tid.x;" : "=r"(tid2));
            const int lane = tid2 & 31;
            const float l0 = __shfl_sync(0xffffffffu, o[8], lane & ~3);
            const float l1 = __shfl_sync(0xffffffffu, o[10], lane & ~3);
            const float i0 = 1.f / l0, i1 = 1.f / l1;
            const uint32_t off = (uint32_t)blockIdx.x * 16384u + (uint32_t)(wg * 4 + t) * 1024u + ((tid2 >> 5) & 3) * 256u + (lane >> 2) * 16u + (lane & 3) * 2u;
            bf16* op = g_O + off;
            *(uint32_t*)(op) = pack_bf16(o[0] * i0, o[1] * i0);
            *(uint32_t*)(op + 128) = pack_bf16(o[2] * i1, o[3] * i1);
            *(uint32_t*)(op + 8) = pack_bf16(o[4] * i0, o[5] * i0);
            *(uint32_t*)(op + 136) = pack_bf16(o[6] * i1, o[7] * i1);
        }
    }
}

struct K3Maps {
    CUtensorMap o;
    CUtensorMap wo[2];
};
#define K3_STAGES 8
#define K3_STAGE_BYTES 24576
#define K3_SMEM (K3_STAGES * K3_STAGE_BYTES + 1024 + 256)

__global__ void __launch_bounds__(288, 1) out_kernel(const __grid_constant__ K3Maps maps, bf16* __restrict__ out) {
    extern __shared__ unsigned char smem_raw[];
    const uint32_t sb = (smem_u32(smem_raw) + 1023) & ~1023u;
    const uint32_t bars = sb + K3_STAGES * K3_STAGE_BYTES;
    const int tid = threadIdx.x, warp = tid >> 5, lane = tid & 31;
    const int mb = blockIdx.x >> 3, nb = blockIdx.x & 7;
    if (tid == 0) {
        for (int i = 0; i < K3_STAGES; i++) {
            mbar_init(bars + i * 8, 1);
            mbar_init(bars + 64 + i * 8, 8);
        }
        asm volatile("fence.mbarrier_init.release.cluster;" ::: "memory");
    }
    __syncthreads();
    if (warp == 8) {
        if (lane == 0) {
            for (int kb = 0; kb < 8; kb++) {
                mbar_expect_tx(bars + kb * 8, K3_STAGE_BYTES);
                tma_2d(sb + kb * K3_STAGE_BYTES + 16384, &maps.wo[0], nb * 64, kb * 64, bars + kb * 8);
            }
            pdl_wait();
            fence_async();
            for (int kb = 0; kb < 8; kb++) tma_2d(sb + kb * K3_STAGE_BYTES, &maps.o, kb * 64, mb * 128, bars + kb * 8);
            for (int kb = 0; kb < 8; kb++) {
                mbar_wait(bars + 64 + kb * 8, 0);
                mbar_expect_tx(bars + kb * 8, K3_STAGE_BYTES);
                tma_2d(sb + kb * K3_STAGE_BYTES, &maps.o, kb * 64, SEQ + mb * 128, bars + kb * 8);
                tma_2d(sb + kb * K3_STAGE_BYTES + 16384, &maps.wo[1], nb * 64, kb * 64, bars + kb * 8);
            }
        }
    } else {
        const int wg = warp >> 2;
        float aa[32], ab[32];
#pragma unroll
        for (int i = 0; i < 32; i++) { aa[i] = 0.f; ab[i] = 0.f; }
        fence_regs<32>(aa);
        fence_regs<32>(ab);
#pragma unroll 1
        for (int kb = 0; kb < 8; kb++) {
            const uint32_t s0 = sb + kb * K3_STAGE_BYTES;
            mbar_wait(bars + kb * 8, 0);
            const uint64_t ad = make_desc(s0 + wg * 8192, 16, 1024, 1);
            const uint64_t bd = make_desc(s0 + 16384, 8192, 1024, 1);
            wg_fence();
#pragma unroll
            for (int kk = 0; kk < 4; kk++) mma_n64_ss(aa, ad + kk * 2, bd + kk * 128);
            wg_commit();
            wg_wait<0>();
            if (lane == 0) mbar_arrive(bars + 64 + kb * 8);
        }
#pragma unroll 1
        for (int kb = 0; kb < 8; kb++) {
            const uint32_t s0 = sb + kb * K3_STAGE_BYTES;
            mbar_wait(bars + kb * 8, 1);
            const uint64_t ad = make_desc(s0 + wg * 8192, 16, 1024, 1);
            const uint64_t bd = make_desc(s0 + 16384, 8192, 1024, 1);
            wg_fence();
#pragma unroll
            for (int kk = 0; kk < 4; kk++) mma_n64_ss(ab, ad + kk * 2, bd + kk * 128);
            wg_commit();
            wg_wait<0>();
        }
        fence_regs<32>(aa);
        fence_regs<32>(ab);
        const int r = lane >> 2, c = lane & 3;
        const int row = mb * 128 + wg * 64 + (warp & 3) * 16 + r;
        const float g0 = __ldcg(g_gate + row), g1 = __ldcg(g_gate + row + 8);
        const float h0 = bf_round(1.f - g0), h1 = bf_round(1.f - g1);
        bf16* op = out + (size_t)row * DM + nb * 64 + 2 * c;
#pragma unroll
        for (int j = 0; j < 8; j++) {
            const float v0 = bf_round(g0 * bf_round(aa[4 * j])) + bf_round(h0 * bf_round(ab[4 * j]));
            const float v1 = bf_round(g0 * bf_round(aa[4 * j + 1])) + bf_round(h0 * bf_round(ab[4 * j + 1]));
            const float v2 = bf_round(g1 * bf_round(aa[4 * j + 2])) + bf_round(h1 * bf_round(ab[4 * j + 2]));
            const float v3 = bf_round(g1 * bf_round(aa[4 * j + 3])) + bf_round(h1 * bf_round(ab[4 * j + 3]));
            *(uint32_t*)(op + j * 8) = pack_bf16(v0, v1);
            *(uint32_t*)(op + 8 * DM + j * 8) = pack_bf16(v2, v3);
        }
    }
}

typedef CUresult (*EncodeFn)(CUtensorMap*, CUtensorMapDataType, cuuint32_t, void*, const cuuint64_t*, const cuuint64_t*, const cuuint32_t*,
                             const cuuint32_t*, CUtensorMapInterleave, CUtensorMapSwizzle, CUtensorMapL2promotion, CUtensorMapFloatOOBfill);

static void encode_2d(EncodeFn fn, CUtensorMap* m, const void* ptr, uint64_t inner, uint64_t outer, uint32_t box_inner, uint32_t box_outer) {
    cuuint64_t dims[2] = {inner, outer};
    cuuint64_t strides[1] = {inner * 2};
    cuuint32_t box[2] = {box_inner, box_outer};
    cuuint32_t es[2] = {1, 1};
    fn(m, CU_TENSOR_MAP_DATA_TYPE_BFLOAT16, 2, (void*)ptr, dims, strides, box, es, CU_TENSOR_MAP_INTERLEAVE_NONE, CU_TENSOR_MAP_SWIZZLE_128B,
       CU_TENSOR_MAP_L2_PROMOTION_L2_256B, CU_TENSOR_MAP_FLOAT_OOB_FILL_NONE);
}

extern "C" void kernel_launch(void* const* d_in, const int* in_sizes, int n_in, void* d_out, int out_size) {
    (void)in_sizes; (void)n_in; (void)out_size;
    static K1Maps m1;
    static K3Maps m3;
    static const void* cached[11] = {0};
    static bool attr_done = false;
    bool same = true;
    for (int i = 0; i < 11; i++) same = same && (cached[i] == d_in[i]);
    if (!same || !attr_done) {
        void* fnp = nullptr;
        cudaDriverEntryPointQueryResult qr;
        cudaGetDriverEntryPoint("cuTensorMapEncodeTiled", &fnp, cudaEnableDefault, &qr);
        EncodeFn fn = (EncodeFn)fnp;
        void* po = nullptr;
        cudaGetSymbolAddress(&po, g_O);
        encode_2d(fn, &m1.x, d_in[0], DM, SEQ, 64, 128);
        encode_2d(fn, &m1.wq[0], d_in[1], DM, DM, 64, 64);
        encode_2d(fn, &m1.wq[1], d_in[6], DM, DM, 64, 64);
        encode_2d(fn, &m1.wkv[0], d_in[2], 16, DM, 64, 64);
        encode_2d(fn, &m1.wkv[1], d_in[3], 16, DM, 64, 64);
        encode_2d(fn, &m1.wkv[2], d_in[7], 16, DM, 64, 64);
        encode_2d(fn, &m1.wkv[3], d_in[8], 16, DM, 64, 64);
        encode_2d(fn, &m3.o, po, DM, 2 * SEQ, 64, 128);
        encode_2d(fn, &m3.wo[0], d_in[4], DM, DM, 64, 64);
        encode_2d(fn, &m3.wo[1], d_in[9], DM, DM, 64, 64);
        cudaFuncSetAttribute(proj_kernel, cudaFuncAttributeMaxDynamicSharedMemorySize, K1_SMEM);
        cudaFuncSetAttribute(attn_kernel, cudaFuncAttributeMaxDynamicSharedMemorySize, K2_SMEM);
        cudaFuncSetAttribute(out_kernel, cudaFuncAttributeMaxDynamicSharedMemorySize, K3_SMEM);
        for (int i = 0; i < 11; i++) cached[i] = d_in[i];
        attr_done = true;
    }
    cudaStream_t st = cudaStreamPerThread;
    proj_kernel<<<128, 288, K1_SMEM, st>>>(m1, (const bf16*)d_in[0], (const bf16*)d_in[10]);

    cudaLaunchAttribute at[1];
    at[0].id = cudaLaunchAttributeProgrammaticStreamSerialization;
    at[0].val.programmaticStreamSerializationAllowed = 1;
    cudaLaunchConfig_t cfg = {};
    cfg.stream = st;
    cfg.attrs = at;
    cfg.numAttrs = 1;
    cfg.gridDim = dim3(128);
    cfg.blockDim = dim3(512);
    cfg.dynamicSmemBytes = K2_SMEM;
    cudaLaunchKernelEx(&cfg, attn_kernel);
    cfg.blockDim = dim3(288);
    cfg.dynamicSmemBytes = K3_SMEM;
    cudaLaunchKernelEx(&cfg, out_kernel, m3, (bf16*)d_out);
}
```

```cpp
#include <cuda_runtime.h>
#include <cuda_bf16.h>
#include <cuda.h>
#include <stdint.h>

typedef __nv_bfloat16 bf16;

#define SEQ 2048
#define DM 512
#define ROWS 65536

__device__ __align__(1024) bf16 g_Q[2 * ROWS * 16];
__device__ __align__(1024) bf16 g_KV[2 * 4 * SEQ * 8];
__device__ __align__(1024) bf16 g_O[2 * ROWS * 16];
__device__ float g_gate[SEQ];
__device__ float g_nrm[128];

#define ts_min(i)
#define ts_max(i)
__device__ __forceinline__ uint32_t smem_u32(const void* p) { return (uint32_t)__cvta_generic_to_shared(p); }
__device__ __forceinline__ uint64_t make_desc(uint32_t saddr, uint32_t lbo, uint32_t sbo, uint32_t swz) {
    uint64_t d = 0;
    d |= (uint64_t)((saddr & 0x3FFFF) >> 4);
    d |= (uint64_t)((lbo & 0x3FFFF) >> 4) << 16;
    d |= (uint64_t)((sbo & 0x3FFFF) >> 4) << 32;
    d |= (uint64_t)swz << 62;
    return d;
}
__device__ __forceinline__ void wg_fence() { asm volatile("wgmma.fence.sync.aligned;" ::: "memory"); }
__device__ __forceinline__ void wg_commit() { asm volatile("wgmma.commit_group.sync.aligned;" ::: "memory"); }
template <int N> __device__ __forceinline__ void wg_wait() { asm volatile("wgmma.wait_group.sync.aligned %0;" ::"n"(N) : "memory"); }
template <int N> __device__ __forceinline__ void fence_regs(float* d) {
#pragma unroll
    for (int i = 0; i < N; i++) asm volatile("" : "+f"(d[i])::"memory");
}
__device__ __forceinline__ void mbar_init(uint32_t bar, uint32_t cnt) { asm volatile("mbarrier.init.shared::cta.b64 [%0], %1;" ::"r"(bar), "r"(cnt)); }
__device__ __forceinline__ void mbar_expect_tx(uint32_t bar, uint32_t bytes) {
    asm volatile("mbarrier.arrive.expect_tx.shared::cta.b64 _, [%0], %1;" ::"r"(bar), "r"(bytes) : "memory");
}
__device__ __forceinline__ void mbar_arrive(uint32_t bar) { asm volatile("mbarrier.arrive.shared::cta.b64 _, [%0];" ::"r"(bar) : "memory"); }
__device__ __forceinline__ void mbar_wait(uint32_t bar, uint32_t parity) {
    asm volatile(
        "{\n.reg .pred p;\n"
        "WAIT_LOOP:\n"
        "mbarrier.try_wait.parity.shared::cta.b64 p, [%0], %1;\n"
        "@p bra DONE;\n"
        "bra WAIT_LOOP;\n"
        "DONE:\n}" ::"r"(bar), "r"(parity) : "memory");
}
__device__ __forceinline__ void mbar_wait_u(uint32_t bar, uint32_t parity) {
    uint32_t ok;
    do {
        asm volatile(
            "{\n.reg .pred p;\nmbarrier.try_wait.parity.shared::cta.b64 p, [%1], %2;\nselp.u32 %0, 1, 0, p;\n}"
            : "=r"(ok) : "r"(bar), "r"(parity) : "memory");
    } while (!__all_sync(0xffffffffu, ok));
}
__device__ __forceinline__ void bulk_g2s(uint32_t dst, const void* src, uint32_t bytes, uint32_t bar) {
    asm volatile("cp.async.bulk.shared::cluster.global.mbarrier::complete_tx::bytes [%0], [%1], %2, [%3];" ::"r"(dst), "l"(src), "r"(bytes), "r"(bar) : "memory");
}
__device__ __forceinline__ void tma_2d(uint32_t dst, const CUtensorMap* map, int c0, int c1, uint32_t bar) {
    asm volatile("cp.async.bulk.tensor.2d.shared::cluster.global.mbarrier::complete_tx::bytes [%0], [%1, {%3, %4}], [%2];" ::"r"(dst), "l"(map), "r"(bar), "r"(c0), "r"(c1) : "memory");
}
__device__ __forceinline__ void l2_prefetch(const void* p, uint32_t bytes) {
    asm volatile("cp.async.bulk.prefetch.L2.global [%0], %1;" ::"l"(p), "r"(bytes) : "memory");
}
__device__ __forceinline__ void pdl_launch() { asm volatile("griddepcontrol.launch_dependents;" ::: "memory"); }
__device__ __forceinline__ void pdl_wait() { asm volatile("griddepcontrol.wait;" ::: "memory"); }
__device__ __forceinline__ void fence_async() { asm volatile("fence.proxy.async;" ::: "memory"); }
__device__ __forceinline__ uint32_t pack_bf16(float lo, float hi) {
    uint32_t r;
    asm("cvt.rn.bf16x2.f32 %0, %1, %2;" : "=r"(r) : "f"(hi), "f"(lo));
    return r;
}
__device__ __forceinline__ float bf_lo(uint32_t u) { return __uint_as_float(u << 16); }
__device__ __forceinline__ float bf_hi(uint32_t u) { return __uint_as_float(u & 0xFFFF0000u); }
__device__ __forceinline__ float bf_round(float x) { return __bfloat162float(__float2bfloat16_rn(x)); }

#define A8(b) "+f"(d[b + 0]), "+f"(d[b + 1]), "+f"(d[b + 2]), "+f"(d[b + 3]), "+f"(d[b + 4]), "+f"(d[b + 5]), "+f"(d[b + 6]), "+f"(d[b + 7])
#define W8(b) "=f"(d[b + 0]), "=f"(d[b + 1]), "=f"(d[b + 2]), "=f"(d[b + 3]), "=f"(d[b + 4]), "=f"(d[b + 5]), "=f"(d[b + 6]), "=f"(d[b + 7])

__device__ __forceinline__ void mma_n136_ss(float* d, uint64_t ad, uint64_t bd) {
    asm volatile(
        "wgmma.mma_async.sync.aligned.m64n136k16.f32.bf16.bf16 "
        "{%0,%1,%2,%3,%4,%5,%6,%7,%8,%9,%10,%11,%12,%13,%14,%15,%16,%17,%18,%19,%20,%21,%22,%23,%24,%25,%26,%27,%28,%29,%30,%31,"
        "%32,%33,%34,%35,%36,%37,%38,%39,%40,%41,%42,%43,%44,%45,%46,%47,%48,%49,%50,%51,%52,%53,%54,%55,%56,%57,%58,%59,%60,%61,%62,%63,"
        "%64,%65,%66,%67}, %68, %69, 1, 1, 1, 0, 1;"
        : A8(0), A8(8), A8(16), A8(24), A8(32), A8(40), A8(48), A8(56), "+f"(d[64]), "+f"(d[65]), "+f"(d[66]), "+f"(d[67])
        : "l"(ad), "l"(bd));
}
__device__ __forceinline__ void mma_n128_ss(float* d, uint64_t ad, uint64_t bd) {
    asm volatile(
        "wgmma.mma_async.sync.aligned.m64n128k16.f32.bf16.bf16 "
        "{%0,%1,%2,%3,%4,%5,%6,%7,%8,%9,%10,%11,%12,%13,%14,%15,%16,%17,%18,%19,%20,%21,%22,%23,%24,%25,%26,%27,%28,%29,%30,%31,"
        "%32,%33,%34,%35,%36,%37,%38,%39,%40,%41,%42,%43,%44,%45,%46,%47,%48,%49,%50,%51,%52,%53,%54,%55,%56,%57,%58,%59,%60,%61,%62,%63}, "
        "%64, %65, 1, 1, 1, 0, 1;"
        : A8(0), A8(8), A8(16), A8(24), A8(32), A8(40), A8(48), A8(56)
        : "l"(ad), "l"(bd));
}
__device__ __forceinline__ void qk_n64(float* d, const uint32_t* a, uint64_t bd) {
    asm volatile(
        "wgmma.mma_async.sync.aligned.m64n64k16.f32.bf16.bf16 "
        "{%0,%1,%2,%3,%4,%5,%6,%7,%8,%9,%10,%11,%12,%13,%14,%15,%16,%17,%18,%19,%20,%21,%22,%23,%24,%25,%26,%27,%28,%29,%30,%31}, "
        "{%32,%33,%34,%35}, %36, 0, 1, 1, 0;"
        : W8(0), W8(8), W8(16), W8(24)
        : "r"(a[0]), "r"(a[1]), "r"(a[2]), "r"(a[3]), "l"(bd));
}
__device__ __forceinline__ void pv_n24(float* d, const uint32_t* a, uint64_t bd) {
    asm volatile(
        "wgmma.mma_async.sync.aligned.m64n24k16.f32.bf16.bf16 {%0,%1,%2,%3,%4,%5,%6,%7,%8,%9,%10,%11}, {%12,%13,%14,%15}, %16, 1, 1, 1, 1;"
        : A8(0), "+f"(d[8]), "+f"(d[9]), "+f"(d[10]), "+f"(d[11])
        : "r"(a[0]), "r"(a[1]), "r"(a[2]), "r"(a[3]), "l"(bd));
}

struct K1Maps {
    CUtensorMap x;
    CUtensorMap wq[2];
    CUtensorMap wkv[4];
};
#define K1_STAGES 5
#define K1_STAGE_BYTES 40960
#define K1_SMEM (K1_STAGES * K1_STAGE_BYTES + 1024 + 256)

__global__ void __launch_bounds__(320, 1) proj_kernel(const __grid_constant__ K1Maps maps, const bf16* __restrict__ x, const bf16* __restrict__ gate_w,
                                                       const bf16* __restrict__ wqa, const bf16* __restrict__ wqb) {
    extern __shared__ unsigned char smem_raw[];
    const uint32_t sb = (smem_u32(smem_raw) + 1023) & ~1023u;
    const uint32_t bars = sb + K1_STAGES * K1_STAGE_BYTES;
    unsigned int* s_max = (unsigned int*)(smem_raw + (bars - smem_u32(smem_raw)) + 128);
    const int tid = threadIdx.x, warp = tid >> 5, lane = tid & 31;
    const int mb = blockIdx.x >> 3, nb = blockIdx.x & 7;
    const int br = nb >> 2;
    ts_min(0); ts_max(16);
    if (tid == 0) {
        for (int i = 0; i < K1_STAGES; i++) {
            mbar_init(bars + i * 8, 1);
            mbar_init(bars + 64 + i * 8, 8);
        }
        *s_max = 0u;
        asm volatile("fence.mbarrier_init.release.cluster;" ::: "memory");
    }
    if (tid == 288) {
        l2_prefetch(x + (size_t)blockIdx.x * 8192, 16384);
        l2_prefetch(wqa + (size_t)blockIdx.x * 2048, 4096);
        l2_prefetch(wqb + (size_t)blockIdx.x * 2048, 4096);
    }
    __syncthreads();
    pdl_launch();
    if (warp == 8) {
        if (lane == 0) {
            for (int kb = 0; kb < 8; kb++) {
                const int st = kb % K1_STAGES;
                if (kb >= K1_STAGES) mbar_wait(bars + 64 + st * 8, 0);
                const uint32_t s0 = sb + st * K1_STAGE_BYTES, fb = bars + st * 8;
                mbar_expect_tx(fb, K1_STAGE_BYTES);
                tma_2d(s0, &maps.x, kb * 64, mb * 128, fb);
                tma_2d(s0 + 16384, &maps.wq[br], (nb & 3) * 128, kb * 64, fb);
                tma_2d(s0 + 24576, &maps.wq[br], (nb & 3) * 128 + 64, kb * 64, fb);
                tma_2d(s0 + 32768, &maps.wkv[nb >> 1], (nb & 1) * 8, kb * 64, fb);
            }
        }
    } else if (warp == 9) {
        const uint4* gw = (const uint4*)(gate_w + lane * 16);
        const uint4 w0 = __ldg(gw), w1 = __ldg(gw + 1);
        const uint32_t wv[8] = {w0.x, w0.y, w0.z, w0.w, w1.x, w1.y, w1.z, w1.w};
#pragma unroll
        for (int half = 0; half < 2; half++) {
            uint4 xa[8][2];
#pragma unroll
            for (int rr = 0; rr < 8; rr++) {
                const uint4* xp = (const uint4*)(x + (size_t)(blockIdx.x * 16 + half * 8 + rr) * DM + lane * 16);
                xa[rr][0] = __ldg(xp);
                xa[rr][1] = __ldg(xp + 1);
            }
#pragma unroll
            for (int rr = 0; rr < 8; rr++) {
                const uint32_t xv[8] = {xa[rr][0].x, xa[rr][0].y, xa[rr][0].z, xa[rr][0].w, xa[rr][1].x, xa[rr][1].y, xa[rr][1].z, xa[rr][1].w};
                float sum = 0.f;
#pragma unroll
                for (int i = 0; i < 8; i++) {
                    sum += bf_round(bf_lo(xv[i]) * bf_lo(wv[i]));
                    sum += bf_round(bf_hi(xv[i]) * bf_hi(wv[i]));
                }
#pragma unroll
                for (int o = 16; o > 0; o >>= 1) sum += __shfl_xor_sync(0xffffffffu, sum, o);
                if (lane == 0) {
                    sum = bf_round(sum);
                    g_gate[blockIdx.x * 16 + half * 8 + rr] = bf_round(1.f / (1.f + __expf(-sum)));
                }
            }
        }
    } else {
        const int wg = warp >> 2;
        float acc[68];
#pragma unroll
        for (int i = 0; i < 68; i++) acc[i] = 0.f;
        fence_regs<68>(acc);
#pragma unroll
        for (int kb = 0; kb < 8; kb++) {
            const int st = kb % K1_STAGES;
            const uint32_t s0 = sb + st * K1_STAGE_BYTES;
            mbar_wait_u(bars + st * 8, kb >= K1_STAGES ? 1 : 0);
            if (kb == 0) { ts_min(12); ts_max(28); }
            if (kb == 4) { ts_min(13); ts_max(29); }
            if (kb == 5) { ts_min(14); ts_max(30); }
            const uint64_t ad = make_desc(s0 + wg * 8192, 16, 1024, 1);
            const uint64_t bd = make_desc(s0 + 16384, 8192, 1024, 1);
            wg_fence();
#pragma unroll
            for (int kk = 0; kk < 4; kk++) mma_n136_ss(acc, ad + kk * 2, bd + kk * 128);
            wg_commit();
            if (kb >= 1 && kb <= 8 - K1_STAGES) {
                wg_wait<1>();
                if (lane == 0) mbar_arrive(bars + 64 + (kb - 1) * 8);
            }
        }
        wg_wait<0>();
        fence_regs<68>(acc);
        ts_min(1); ts_max(17);
        const int r = lane >> 2, c = lane & 3;
        const int row = mb * 128 + wg * 64 + (warp & 3) * 16 + r;
        const uint32_t k0 = pack_bf16(acc[64], acc[65]), k1 = pack_bf16(acc[66], acc[67]);
        bf16* kvp = g_KV + (size_t)br * 65536 + (row >> 8) * 8192 + (nb & 3) * 2048 + (row & 255) * 8 + 2 * c;
        *(uint32_t*)kvp = k0;
        *(uint32_t*)(kvp + 64) = k1;
        const float qs = 0.25f * 1.4426950408889634f;
        bf16* qp = g_Q + (size_t)br * ROWS * 16 + (size_t)row * DM + (nb & 3) * 128 + 4 * c;
#pragma unroll
        for (int h = 0; h < 8; h++) {
            const float* a = acc + h * 8;
            uint2 v0 = make_uint2(pack_bf16(a[0] * qs, a[1] * qs), pack_bf16(a[4] * qs, a[5] * qs));
            uint2 v1 = make_uint2(pack_bf16(a[2] * qs, a[3] * qs), pack_bf16(a[6] * qs, a[7] * qs));
            *(uint2*)(qp + h * 16) = v0;
            *(uint2*)(qp + 8 * DM + h * 16) = v1;
        }
        float m;
        if (((nb >> 1) & 1) == 0) {
            float n0 = bf_lo(k0) * bf_lo(k0) + bf_hi(k0) * bf_hi(k0);
            float n1 = bf_lo(k1) * bf_lo(k1) + bf_hi(k1) * bf_hi(k1);
            n0 += __shfl_xor_sync(0xffffffffu, n0, 1);
            n1 += __shfl_xor_sync(0xffffffffu, n1, 1);
            n0 += __shfl_xor_sync(0xffffffffu, n0, 2);
            n1 += __shfl_xor_sync(0xffffffffu, n1, 2);
            m = __uint_as_float(max(__float_as_uint(n0), __float_as_uint(n1)));
        } else {
            uint32_t u = max(max((k0 << 16) & 0x7FFFFFFFu, k0 & 0x7FFF0000u), max((k1 << 16) & 0x7FFFFFFFu, k1 & 0x7FFF0000u));
            m = __uint_as_float(u);
        }
        unsigned int mu = __reduce_max_sync(0xffffffffu, __float_as_uint(m));
        if (lane == 0) atomicMax(s_max, mu);
        asm volatile("bar.sync 1, 256;" ::: "memory");
        if (tid == 0) g_nrm[blockIdx.x] = __uint_as_float(*s_max);
        ts_min(2); ts_max(18);
    }
}

__device__ __forceinline__ float ex2(float x) {
    float e;
    asm("ex2.approx.ftz.f32 %0, %1;" : "=f"(e) : "f"(x));
    return e;
}
__device__ __forceinline__ uint32_t exp_pair_mufu(float x0, float x1) { return pack_bf16(ex2(x0), ex2(x1)); }

#define MAGIC0 (98304.0f + 127.0f - 75.0f / 128.0f)
#define MAGIC1 (98304.0f + 127.0f - 75.0f / 128.0f - 143.5f)
template <int PRM>
__device__ __forceinline__ uint32_t exp_pair_poly(float x0, float x1, uint32_t c3f) {
    float t0 = x0 + MAGIC0;
    float t1 = x1 + (PRM ? MAGIC0 : MAGIC1);
    uint32_t L, y2, E, r;
    if (PRM)
        asm("prmt.b32 %0, %1, %2, 0x5410;" : "=r"(L) : "r"(__float_as_uint(t0)), "r"(__float_as_uint(t1)));
    else
        L = __float_as_uint(t1) * 65536u + __float_as_uint(t0);
    asm("lop3.b32 %0, %1, 0x007F007F, %2, 0xEA;" : "=r"(y2) : "r"(L), "r"(c3f));
    E = L & 0x7F807F80u;
    asm("fma.rn.bf16x2 %0, %1, %2, %3;" : "=r"(r) : "r"(L), "r"(y2), "r"(E));
    return r;
}
#define EXP_MASK 0x4949u
template <int BASE>
__device__ __forceinline__ void exp_half(const float* s, uint32_t* p, uint32_t c3f) {
#pragma unroll
    for (int i = 0; i < 8; i++) {
        if ((EXP_MASK >> (BASE + i)) & 1) p[i] = exp_pair_mufu(s[2 * i], s[2 * i + 1]);
        else if (i & 1) p[i] = exp_pair_poly<1>(s[2 * i], s[2 * i + 1], c3f);
        else p[i] = exp_pair_poly<0>(s[2 * i], s[2 * i + 1], c3f);
    }
}

#define CHUNK_BYTES 20480
#define SM_BAR 163840
#define K2_SMEM (163840 + 128 + 1024)

__device__ __forceinline__ void attn_tile_slow(const uint32_t* qq, uint64_t kd0, uint64_t vd0, float* o, float* s, uint32_t* p) {
    float m0 = -INFINITY, m1 = -INFINITY;
#pragma unroll 1
    for (int ch = 0; ch < 32; ch++) {
        wg_fence();
        qk_n64(s, qq, kd0 + (uint64_t)((ch >> 2) * 1280 + (ch & 3) * 64));
        wg_commit();
        wg_wait<0>();
        fence_regs<32>(s);
#pragma unroll
        for (int j = 0; j < 8; j++) {
            m0 = fmaxf(m0, fmaxf(s[4 * j], s[4 * j + 1]));
            m1 = fmaxf(m1, fmaxf(s[4 * j + 2], s[4 * j + 3]));
        }
    }
    m0 = fmaxf(m0, __shfl_xor_sync(0xffffffffu, m0, 1));
    m1 = fmaxf(m1, __shfl_xor_sync(0xffffffffu, m1, 1));
    m0 = fmaxf(m0, __shfl_xor_sync(0xffffffffu, m0, 2));
    m1 = fmaxf(m1, __shfl_xor_sync(0xffffffffu, m1, 2));
#pragma unroll 1
    for (int ch = 0; ch < 32; ch++) {
        wg_fence();
        qk_n64(s, qq, kd0 + (uint64_t)((ch >> 2) * 1280 + (ch & 3) * 64));
        wg_commit();
        wg_wait<0>();
        fence_regs<32>(s);
#pragma unroll
        for (int j = 0; j < 8; j++) {
            p[2 * j] = exp_pair_mufu(s[4 * j] - m0, s[4 * j + 1] - m0);
            p[2 * j + 1] = exp_pair_mufu(s[4 * j + 2] - m1, s[4 * j + 3] - m1);
        }
        wg_fence();
#pragma unroll
        for (int j = 0; j < 4; j++) pv_n24(o, p + 4 * j, vd0 + (uint64_t)((ch >> 2) * 1280 + (ch & 3) * 64 + 16 * j));
        wg_commit();
        wg_wait<0>();
        fence_regs<12>(o);
    }
}

__global__ void __launch_bounds__(512, 1) attn_kernel(const bf16* __restrict__ woa, const bf16* __restrict__ wob) {
    extern __shared__ unsigned char smem_raw[];
    const uint32_t sb = (smem_u32(smem_raw) + 1023) & ~1023u;
    unsigned char* smem = smem_raw + (sb - smem_u32(smem_raw));
    const int tid = threadIdx.x;
    const int br = blockIdx.x >> 6;
    ts_min(3); ts_max(19);
    if (tid == 0) {
        for (int i = 0; i < 8; i++) mbar_init(sb + SM_BAR + i * 8, 1);
        asm volatile("fence.mbarrier_init.release.cluster;" ::: "memory");
    }
#pragma unroll
    for (int i = 0; i < 4; i++) *(uint4*)(smem + (2 * i + (tid >> 8)) * CHUNK_BYTES + 16384 + (tid & 255) * 16) = make_uint4(0x00003F80u, 0, 0, 0);
    if (tid == 32) {
        l2_prefetch(woa + (size_t)blockIdx.x * 2048, 4096);
        l2_prefetch(wob + (size_t)blockIdx.x * 2048, 4096);
    }
    asm volatile("fence.proxy.async.shared::cta;" ::: "memory");
    __syncthreads();
    pdl_launch();
    pdl_wait();
    ts_min(4); ts_max(20);
    if (tid == 0) {
        fence_async();
        const unsigned char* src = (const unsigned char*)g_KV + (size_t)br * 131072;
        for (int g = 0; g < 8; g++) {
            const uint32_t bar = sb + SM_BAR + g * 8;
            mbar_expect_tx(bar, 16384);
            bulk_g2s(sb + g * CHUNK_BYTES, src + g * 16384, 16384, bar);
        }
    }
    const int wg = __shfl_sync(0xffffffffu, tid >> 7, 0);
    volatile float* s_kmax2 = (volatile float*)(smem + SM_BAR + 64) + (tid >> 5);
    {
        const int lane = tid & 31;
        const unsigned int a = __float_as_uint(g_nrm[(lane & 15) * 8 + br * 4 + (lane >> 4)]);
        const unsigned int b = __float_as_uint(g_nrm[(lane & 15) * 8 + br * 4 + 2 + (lane >> 4)]);
        unsigned int h = a;
#pragma unroll
        for (int o = 8; o > 0; o >>= 1) h = max(h, __shfl_xor_sync(0xffffffffu, h, o));
        float kmax2 = __uint_as_float(h) + __uint_as_float(__shfl_xor_sync(0xffffffffu, h, 16));
        const float vmax = __uint_as_float(__reduce_max_sync(0xffffffffu, b));
        if (!(vmax <= 1.0e15f)) kmax2 = __uint_as_float(0x7FC00000u);
        if (lane == 0) *s_kmax2 = kmax2;
        __syncwarp();
    }
    uint32_t c3f = 0x3F003F00u;
    asm volatile("" : "+r"(c3f));
    const uint64_t kd0 = make_desc(sb, 4096, 128, 0);
    const uint64_t vd0 = make_desc(sb + 8192, 128, 4096, 0);

#pragma unroll 1
    for (int t = 0; t < 4; t++) {
        uint32_t q[4];
        uint32_t any_unsafe;
        {
            const uint32_t off = (uint32_t)blockIdx.x * 16384u + (uint32_t)(wg * 4 + t) * 1024u + ((tid >> 5) & 3) * 256u + (tid & 31) * 4u;
            const uint2 a = *(const uint2*)(g_Q + off), b = *(const uint2*)(g_Q + off + 128);
            q[0] = a.x; q[2] = a.y; q[1] = b.x; q[3] = b.y;
            float n0 = bf_lo(q[0]) * bf_lo(q[0]) + bf_hi(q[0]) * bf_hi(q[0]) + bf_lo(q[2]) * bf_lo(q[2]) + bf_hi(q[2]) * bf_hi(q[2]);
            float n1 = bf_lo(q[1]) * bf_lo(q[1]) + bf_hi(q[1]) * bf_hi(q[1]) + bf_lo(q[3]) * bf_lo(q[3]) + bf_hi(q[3]) * bf_hi(q[3]);
            n0 += __shfl_xor_sync(0xffffffffu, n0, 1);
            n1 += __shfl_xor_sync(0xffffffffu, n1, 1);
            n0 += __shfl_xor_sync(0xffffffffu, n0, 2);
            n1 += __shfl_xor_sync(0xffffffffu, n1, 2);
            const float kmax2 = *s_kmax2;
            const bool unsafe = !(n0 * kmax2 <= 3600.f) || !(n1 * kmax2 <= 3600.f);
            asm volatile(
                "{\n.reg .pred p, q;\nsetp.ne.u32 q, %1, 0;\nbar.red.or.pred p, %2, 128, q;\nselp.u32 %0, 1, 0, p;\n}"
                : "=r"(any_unsafe) : "r"((uint32_t)unsafe), "r"(wg + 1) : "memory");
        }
        float o[12];
        float s0[32], s1[32];
        uint32_t p[16];
#pragma unroll
        for (int i = 0; i < 12; i++) o[i] = 0.f;
        fence_regs<12>(o);
        if (__any_sync(0xffffffffu, any_unsafe)) {
            for (int g = 0; g < 8; g++) mbar_wait_u(sb + SM_BAR + g * 8, 0);
            attn_tile_slow(q, kd0, vd0, o, s0, p);
        } else {
            mbar_wait_u(sb + SM_BAR, 0);
            if (t == 0) { ts_min(5); ts_max(21); }
            wg_fence();
            qk_n64(s0, q, kd0);
            wg_commit();
            wg_wait<0>();
            fence_regs<32>(s0);
            uint64_t kd = kd0, vd = vd0;
#pragma unroll 1
            for (uint32_t it = 0; it < 16; it++) {
                wg_fence();
                qk_n64(s1, q, kd + 64);
                wg_commit();
                exp_half<0>(s0, p, c3f);
                wg_fence();
                pv_n24(o, p, vd);
                pv_n24(o, p + 4, vd + 16);
                wg_commit();
                wg_wait<2>();
                exp_half<8>(s0 + 16, p + 8, c3f);
                wg_fence();
                pv_n24(o, p + 8, vd + 32);
                pv_n24(o, p + 12, vd + 48);
                wg_commit();
                wg_wait<1>();
                fence_regs<32>(s1);
                if (it & 1) mbar_wait_u(sb + SM_BAR + (((it + 1) >> 1) & 7) * 8, 0);
                kd = (it == 15) ? kd0 : kd + ((it & 1) ? 1152 : 128);
                wg_fence();
                qk_n64(s0, q, kd);
                wg_commit();
                exp_half<0>(s1, p, c3f);
                wg_fence();
                pv_n24(o, p, vd + 64);
                pv_n24(o, p + 4, vd + 80);
                wg_commit();
                wg_wait<2>();
                exp_half<8>(s1 + 16, p + 8, c3f);
                wg_fence();
                pv_n24(o, p + 8, vd + 96);
                pv_n24(o, p + 12, vd + 112);
                wg_commit();
                wg_wait<1>();
                fence_regs<32>(s0);
                vd += (it & 1) ? 1152 : 128;
            }
            wg_wait<0>();
            fence_regs<12>(o);
        }
        {
            int tid2;
            asm volatile("mov.u32 %0, %%tid.x;" : "=r"(tid2));
            const int lane = tid2 & 31;
            const float l0 = __shfl_sync(0xffffffffu, o[8], lane & ~3);
            const float l1 = __shfl_sync(0xffffffffu, o[10], lane & ~3);
            const float i0 = 1.f / l0, i1 = 1.f / l1;
            const uint32_t off = (uint32_t)blockIdx.x * 16384u + (uint32_t)(wg * 4 + t) * 1024u + ((tid2 >> 5) & 3) * 256u + (lane >> 2) * 16u + (lane & 3) * 2u;
            bf16* op = g_O + off;
            *(uint32_t*)(op) = pack_bf16(o[0] * i0, o[1] * i0);
            *(uint32_t*)(op + 128) = pack_bf16(o[2] * i1, o[3] * i1);
            *(uint32_t*)(op + 8) = pack_bf16(o[4] * i0, o[5] * i0);
            *(uint32_t*)(op + 136) = pack_bf16(o[6] * i1, o[7] * i1);
        }
    }
    ts_min(6); ts_max(22);
}

struct K3Maps {
    CUtensorMap o;
    CUtensorMap wo[2];
};
#define K3_STAGES 4
#define K3_STAGE_BYTES 49152
#define K3_XCH (K3_STAGES * K3_STAGE_BYTES)
#define K3_SMEM (K3_XCH + 16384 + 1024 + 256)

__global__ void __launch_bounds__(288, 1) out_kernel(const __grid_constant__ K3Maps maps, bf16* __restrict__ out) {
    extern __shared__ unsigned char smem_raw[];
    const uint32_t sb = (smem_u32(smem_raw) + 1023) & ~1023u;
    unsigned char* smem = smem_raw + (sb - smem_u32(smem_raw));
    const uint32_t bars = sb + K3_XCH + 16384;
    const int tid = threadIdx.x, warp = tid >> 5, lane = tid & 31;
    const int mb = blockIdx.x >> 2, nb = blockIdx.x & 3;
    ts_min(7); ts_max(23);
    if (tid == 0) {
        for (int i = 0; i < 2 * K3_STAGES; i++) {
            mbar_init(bars + i * 8, 1);
            mbar_init(bars + 64 + i * 8, 4);
        }
        asm volatile("fence.mbarrier_init.release.cluster;" ::: "memory");
    }
    __syncthreads();
    if (warp == 8) {
        if (lane == 0) {
            for (int i = 0; i < 2 * K3_STAGES; i++) {
                const int kb = i >> 1, b = i & 1;
                const uint32_t s0 = sb + kb * K3_STAGE_BYTES + b * 24576;
                mbar_expect_tx(bars + i * 8, 24576);
                tma_2d(s0 + 8192, &maps.wo[b], nb * 128, kb * 64, bars + i * 8);
                tma_2d(s0 + 16384, &maps.wo[b], nb * 128 + 64, kb * 64, bars + i * 8);
            }
            pdl_wait();
            fence_async();
            for (int i = 0; i < 2 * K3_STAGES; i++) {
                const int kb = i >> 1, b = i & 1;
                tma_2d(sb + kb * K3_STAGE_BYTES + b * 24576, &maps.o, kb * 64, b * SEQ + mb * 64, bars + i * 8);
            }
            for (int i = 0; i < 2 * K3_STAGES; i++) {
                const int kb = K3_STAGES + (i >> 1), b = i & 1;
                const uint32_t s0 = sb + (i >> 1) * K3_STAGE_BYTES + b * 24576;
                mbar_wait(bars + 64 + i * 8, 0);
                mbar_expect_tx(bars + i * 8, 24576);
                tma_2d(s0, &maps.o, kb * 64, b * SEQ + mb * 64, bars + i * 8);
                tma_2d(s0 + 8192, &maps.wo[b], nb * 128, kb * 64, bars + i * 8);
                tma_2d(s0 + 16384, &maps.wo[b], nb * 128 + 64, kb * 64, bars + i * 8);
            }
        }
    } else {
        const int wg = warp >> 2;
        float acc[64];
#pragma unroll
        for (int i = 0; i < 64; i++) acc[i] = 0.f;
        fence_regs<64>(acc);
        const int r = lane >> 2, c = lane & 3;
        const int lrow = (warp & 3) * 16 + r;
        float g0 = 0.f, g1 = 0.f;
#pragma unroll
        for (int kb = 0; kb < 8; kb++) {
            const int st = kb % K3_STAGES;
            const uint32_t s0 = sb + st * K3_STAGE_BYTES + wg * 24576;
            mbar_wait_u(bars + (st * 2 + wg) * 8, kb >= K3_STAGES ? 1 : 0);
            if (kb == 0) {
                ts_min(8); ts_max(24);
                g0 = __ldcg(g_gate + mb * 64 + lrow);
                g1 = __ldcg(g_gate + mb * 64 + lrow + 8);
            }
            const uint64_t ad = make_desc(s0, 16, 1024, 1);
            const uint64_t bd = make_desc(s0 + 8192, 8192, 1024, 1);
            wg_fence();
#pragma unroll
            for (int kk = 0; kk < 4; kk++) mma_n128_ss(acc, ad + kk * 2, bd + kk * 128);
            wg_commit();
            if (kb >= 1 && kb <= K3_STAGES) {
                wg_wait<1>();
                if (lane == 0) mbar_arrive(bars + 64 + ((kb - 1) * 2 + wg) * 8);
            }
        }
        wg_wait<0>();
        fence_regs<64>(acc);
        ts_min(9); ts_max(25);
        if (wg) { g0 = bf_round(1.f - g0); g1 = bf_round(1.f - g1); }
        uint32_t t[32];
#pragma unroll
        for (int j = 0; j < 16; j++) {
            t[2 * j] = pack_bf16(g0 * bf_round(acc[4 * j]), g0 * bf_round(acc[4 * j + 1]));
            t[2 * j + 1] = pack_bf16(g1 * bf_round(acc[4 * j + 2]), g1 * bf_round(acc[4 * j + 3]));
        }
        uint32_t* xch = (uint32_t*)(smem + K3_XCH);
        const int lt = tid & 127;
#pragma unroll
        for (int j = 0; j < 16; j++) xch[(wg * 16 + j) * 128 + lt] = wg ? t[j] : t[16 + j];
        asm volatile("bar.sync 1, 256;" ::: "memory");
        unsigned char* ot = smem + wg * 16384;
#pragma unroll
        for (int j = 0; j < 16; j++) {
            const uint32_t mine = wg ? t[16 + j] : t[j];
            const uint32_t other = xch[((wg ^ 1) * 16 + j) * 128 + lt];
            const uint32_t v = pack_bf16(bf_lo(mine) + bf_lo(other), bf_hi(mine) + bf_hi(other));
            *(uint32_t*)(ot + (lrow + (j & 1) * 8) * 144 + (j >> 1) * 16 + c * 4) = v;
        }
        asm volatile("bar.sync %0, 128;" ::"r"(wg + 2) : "memory");
#pragma unroll
        for (int i = 0; i < 4; i++) {
            const int idx = i * 128 + lt, row = idx >> 3, ch = idx & 7;
            const uint4 v = *(const uint4*)(ot + row * 144 + ch * 16);
            *(uint4*)(out + (size_t)(mb * 64 + row) * DM + nb * 128 + wg * 64 + ch * 8) = v;
        }
        ts_min(10); ts_max(26);
    }
}

typedef CUresult (*EncodeFn)(CUtensorMap*, CUtensorMapDataType, cuuint32_t, void*, const cuuint64_t*, const cuuint64_t*, const cuuint32_t*,
                             const cuuint32_t*, CUtensorMapInterleave, CUtensorMapSwizzle, CUtensorMapL2promotion, CUtensorMapFloatOOBfill);

static void encode_2d(EncodeFn fn, CUtensorMap* m, const void* ptr, uint64_t inner, uint64_t outer, uint32_t box_inner, uint32_t box_outer) {
    cuuint64_t dims[2] = {inner, outer};
    cuuint64_t strides[1] = {inner * 2};
    cuuint32_t box[2] = {box_inner, box_outer};
    cuuint32_t es[2] = {1, 1};
    fn(m, CU_TENSOR_MAP_DATA_TYPE_BFLOAT16, 2, (void*)ptr, dims, strides, box, es, CU_TENSOR_MAP_INTERLEAVE_NONE, CU_TENSOR_MAP_SWIZZLE_128B,
       CU_TENSOR_MAP_L2_PROMOTION_L2_256B, CU_TENSOR_MAP_FLOAT_OOB_FILL_NONE);
}

extern "C" void kernel_launch(void* const* d_in, const int* in_sizes, int n_in, void* d_out, int out_size) {
    (void)in_sizes; (void)n_in; (void)out_size;
    static K1Maps m1;
    static K3Maps m3;
    static const void* cached[11] = {0};
    static bool attr_done = false;
    bool same = true;
    for (int i = 0; i < 11; i++) same = same && (cached[i] == d_in[i]);
    if (!same || !attr_done) {
        void* fnp = nullptr;
        cudaDriverEntryPointQueryResult qr;
        cudaGetDriverEntryPoint("cuTensorMapEncodeTiled", &fnp, cudaEnableDefault, &qr);
        EncodeFn fn = (EncodeFn)fnp;
        void* po = nullptr;
        cudaGetSymbolAddress(&po, g_O);
        encode_2d(fn, &m1.x, d_in[0], DM, SEQ, 64, 128);
        encode_2d(fn, &m1.wq[0], d_in[1], DM, DM, 64, 64);
        encode_2d(fn, &m1.wq[1], d_in[6], DM, DM, 64, 64);
        encode_2d(fn, &m1.wkv[0], d_in[2], 16, DM, 64, 64);
        encode_2d(fn, &m1.wkv[1], d_in[3], 16, DM, 64, 64);
        encode_2d(fn, &m1.wkv[2], d_in[7], 16, DM, 64, 64);
        encode_2d(fn, &m1.wkv[3], d_in[8], 16, DM, 64, 64);
        encode_2d(fn, &m3.o, po, DM, 2 * SEQ, 64, 64);
        encode_2d(fn, &m3.wo[0], d_in[4], DM, DM, 64, 64);
        encode_2d(fn, &m3.wo[1], d_in[9], DM, DM, 64, 64);
        cudaFuncSetAttribute(proj_kernel, cudaFuncAttributeMaxDynamicSharedMemorySize, K1_SMEM);
        cudaFuncSetAttribute(attn_kernel, cudaFuncAttributeMaxDynamicSharedMemorySize, K2_SMEM);
        cudaFuncSetAttribute(out_kernel, cudaFuncAttributeMaxDynamicSharedMemorySize, K3_SMEM);
        for (int i = 0; i < 11; i++) cached[i] = d_in[i];
        attr_done = true;
    }
    cudaStream_t st = cudaStreamPerThread;
    proj_kernel<<<128, 320, K1_SMEM, st>>>(m1, (const bf16*)d_in[0], (const bf16*)d_in[10], (const bf16*)d_in[1], (const bf16*)d_in[6]);

    cudaLaunchAttribute at[1];
    at[0].id = cudaLaunchAttributeProgrammaticStreamSerialization;
    at[0].val.programmaticStreamSerializationAllowed = 1;
    cudaLaunchConfig_t cfg = {};
    cfg.stream = st;
    cfg.attrs = at;
    cfg.numAttrs = 1;
    cfg.gridDim = dim3(128);
    cfg.blockDim = dim3(512);
    cfg.dynamicSmemBytes = K2_SMEM;
    cudaLaunchKernelEx(&cfg, attn_kernel, (const bf16*)d_in[4], (const bf16*)d_in[9]);
    cfg.blockDim = dim3(288);
    cfg.dynamicSmemBytes = K3_SMEM;
    cudaLaunchKernelEx(&cfg, out_kernel, m3, (bf16*)d_out);
}
```

```cpp
#include <cuda_runtime.h>
#include <cuda_bf16.h>
#include <cuda.h>
#include <stdint.h>

typedef __nv_bfloat16 bf16;

#define SEQ 2048
#define DM 512
#define ROWS 65536

__device__ __align__(1024) bf16 g_KV[2 * 4 * SEQ * 8];
__device__ __align__(1024) bf16 g_O[2 * ROWS * 16];
__device__ float g_gate[SEQ];
__device__ __align__(16) float g_nrm[128];
__device__ unsigned int g_ctr[32];

#define ts_min(i)
#define ts_max(i)
__device__ __forceinline__ uint32_t smem_u32(const void* p) { return (uint32_t)__cvta_generic_to_shared(p); }
__device__ __forceinline__ uint64_t make_desc(uint32_t saddr, uint32_t lbo, uint32_t sbo, uint32_t swz) {
    uint64_t d = 0;
    d |= (uint64_t)((saddr & 0x3FFFF) >> 4);
    d |= (uint64_t)((lbo & 0x3FFFF) >> 4) << 16;
    d |= (uint64_t)((sbo & 0x3FFFF) >> 4) << 32;
    d |= (uint64_t)swz << 62;
    return d;
}
__device__ __forceinline__ void wg_fence() { asm volatile("wgmma.fence.sync.aligned;" ::: "memory"); }
__device__ __forceinline__ void wg_commit() { asm volatile("wgmma.commit_group.sync.aligned;" ::: "memory"); }
template <int N> __device__ __forceinline__ void wg_wait() { asm volatile("wgmma.wait_group.sync.aligned %0;" ::"n"(N) : "memory"); }
template <int N> __device__ __forceinline__ void fence_regs(float* d) {
#pragma unroll
    for (int i = 0; i < N; i++) asm volatile("" : "+f"(d[i])::"memory");
}
__device__ __forceinline__ void mbar_init(uint32_t bar, uint32_t cnt) { asm volatile("mbarrier.init.shared::cta.b64 [%0], %1;" ::"r"(bar), "r"(cnt)); }
__device__ __forceinline__ void mbar_expect_tx(uint32_t bar, uint32_t bytes) {
    asm volatile("mbarrier.arrive.expect_tx.shared::cta.b64 _, [%0], %1;" ::"r"(bar), "r"(bytes) : "memory");
}
__device__ __forceinline__ void mbar_arrive(uint32_t bar) { asm volatile("mbarrier.arrive.shared::cta.b64 _, [%0];" ::"r"(bar) : "memory"); }
__device__ __forceinline__ void mbar_wait(uint32_t bar, uint32_t parity) {
    asm volatile(
        "{\n.reg .pred p;\n"
        "WAIT_LOOP:\n"
        "mbarrier.try_wait.parity.shared::cta.b64 p, [%0], %1;\n"
        "@p bra DONE;\n"
        "bra WAIT_LOOP;\n"
        "DONE:\n}" ::"r"(bar), "r"(parity) : "memory");
}
__device__ __forceinline__ void mbar_wait_u(uint32_t bar, uint32_t parity) {
    uint32_t ok;
    do {
        asm volatile(
            "{\n.reg .pred p;\nmbarrier.try_wait.parity.shared::cta.b64 p, [%1], %2;\nselp.u32 %0, 1, 0, p;\n}"
            : "=r"(ok) : "r"(bar), "r"(parity) : "memory");
    } while (!__all_sync(0xffffffffu, ok));
}
__device__ __forceinline__ void bulk_g2s(uint32_t dst, const void* src, uint32_t bytes, uint32_t bar) {
    asm volatile("cp.async.bulk.shared::cluster.global.mbarrier::complete_tx::bytes [%0], [%1], %2, [%3];" ::"r"(dst), "l"(src), "r"(bytes), "r"(bar) : "memory");
}
__device__ __forceinline__ void tma_2d(uint32_t dst, const CUtensorMap* map, int c0, int c1, uint32_t bar) {
    asm volatile("cp.async.bulk.tensor.2d.shared::cluster.global.mbarrier::complete_tx::bytes [%0], [%1, {%3, %4}], [%2];" ::"r"(dst), "l"(map), "r"(bar), "r"(c0), "r"(c1) : "memory");
}
__device__ __forceinline__ void l2_prefetch(const void* p, uint32_t bytes) {
    asm volatile("cp.async.bulk.prefetch.L2.global [%0], %1;" ::"l"(p), "r"(bytes) : "memory");
}
__device__ __forceinline__ void pdl_launch() { asm volatile("griddepcontrol.launch_dependents;" ::: "memory"); }
__device__ __forceinline__ void pdl_wait() { asm volatile("griddepcontrol.wait;" ::: "memory"); }
__device__ __forceinline__ void fence_async() { asm volatile("fence.proxy.async;" ::: "memory"); }
__device__ __forceinline__ uint32_t pack_bf16(float lo, float hi) {
    uint32_t r;
    asm("cvt.rn.bf16x2.f32 %0, %1, %2;" : "=r"(r) : "f"(hi), "f"(lo));
    return r;
}
__device__ __forceinline__ float bf_lo(uint32_t u) { return __uint_as_float(u << 16); }
__device__ __forceinline__ float bf_hi(uint32_t u) { return __uint_as_float(u & 0xFFFF0000u); }
__device__ __forceinline__ float bf_round(float x) { return __bfloat162float(__float2bfloat16_rn(x)); }

#define A8(b) "+f"(d[b + 0]), "+f"(d[b + 1]), "+f"(d[b + 2]), "+f"(d[b + 3]), "+f"(d[b + 4]), "+f"(d[b + 5]), "+f"(d[b + 6]), "+f"(d[b + 7])
#define W8(b) "=f"(d[b + 0]), "=f"(d[b + 1]), "=f"(d[b + 2]), "=f"(d[b + 3]), "=f"(d[b + 4]), "=f"(d[b + 5]), "=f"(d[b + 6]), "=f"(d[b + 7])

__device__ __forceinline__ void mma_n136_ss(float* d, uint64_t ad, uint64_t bd) {
    asm volatile(
        "wgmma.mma_async.sync.aligned.m64n136k16.f32.bf16.bf16 "
        "{%0,%1,%2,%3,%4,%5,%6,%7,%8,%9,%10,%11,%12,%13,%14,%15,%16,%17,%18,%19,%20,%21,%22,%23,%24,%25,%26,%27,%28,%29,%30,%31,"
        "%32,%33,%34,%35,%36,%37,%38,%39,%40,%41,%42,%43,%44,%45,%46,%47,%48,%49,%50,%51,%52,%53,%54,%55,%56,%57,%58,%59,%60,%61,%62,%63,"
        "%64,%65,%66,%67}, %68, %69, 1, 1, 1, 0, 1;"
        : A8(0), A8(8), A8(16), A8(24), A8(32), A8(40), A8(48), A8(56), "+f"(d[64]), "+f"(d[65]), "+f"(d[66]), "+f"(d[67])
        : "l"(ad), "l"(bd));
}
__device__ __forceinline__ void mma_n128_ss(float* d, uint64_t ad, uint64_t bd) {
    asm volatile(
        "wgmma.mma_async.sync.aligned.m64n128k16.f32.bf16.bf16 "
        "{%0,%1,%2,%3,%4,%5,%6,%7,%8,%9,%10,%11,%12,%13,%14,%15,%16,%17,%18,%19,%20,%21,%22,%23,%24,%25,%26,%27,%28,%29,%30,%31,"
        "%32,%33,%34,%35,%36,%37,%38,%39,%40,%41,%42,%43,%44,%45,%46,%47,%48,%49,%50,%51,%52,%53,%54,%55,%56,%57,%58,%59,%60,%61,%62,%63}, "
        "%64, %65, 1, 1, 1, 0, 1;"
        : A8(0), A8(8), A8(16), A8(24), A8(32), A8(40), A8(48), A8(56)
        : "l"(ad), "l"(bd));
}
__device__ __forceinline__ void qk_n64(float* d, const uint32_t* a, uint64_t bd) {
    asm volatile(
        "wgmma.mma_async.sync.aligned.m64n64k16.f32.bf16.bf16 "
        "{%0,%1,%2,%3,%4,%5,%6,%7,%8,%9,%10,%11,%12,%13,%14,%15,%16,%17,%18,%19,%20,%21,%22,%23,%24,%25,%26,%27,%28,%29,%30,%31}, "
        "{%32,%33,%34,%35}, %36, 0, 1, 1, 0;"
        : W8(0), W8(8), W8(16), W8(24)
        : "r"(a[0]), "r"(a[1]), "r"(a[2]), "r"(a[3]), "l"(bd));
}
__device__ __forceinline__ void pv_n24(float* d, const uint32_t* a, uint64_t bd) {
    asm volatile(
        "wgmma.mma_async.sync.aligned.m64n24k16.f32.bf16.bf16 {%0,%1,%2,%3,%4,%5,%6,%7,%8,%9,%10,%11}, {%12,%13,%14,%15}, %16, 1, 1, 1, 1;"
        : A8(0), "+f"(d[8]), "+f"(d[9]), "+f"(d[10]), "+f"(d[11])
        : "r"(a[0]), "r"(a[1]), "r"(a[2]), "r"(a[3]), "l"(bd));
}

__device__ __forceinline__ float ex2(float x) {
    float e;
    asm("ex2.approx.ftz.f32 %0, %1;" : "=f"(e) : "f"(x));
    return e;
}
__device__ __forceinline__ uint32_t exp_pair_mufu(float x0, float x1) { return pack_bf16(ex2(x0), ex2(x1)); }

#define MAGIC0 (98304.0f + 127.0f - 75.0f / 128.0f)
#define MAGIC1 (98304.0f + 127.0f - 75.0f / 128.0f - 143.5f)
template <int PRM>
__device__ __forceinline__ uint32_t exp_pair_poly(float x0, float x1, uint32_t c3f) {
    float t0 = x0 + MAGIC0;
    float t1 = x1 + (PRM ? MAGIC0 : MAGIC1);
    uint32_t L, y2, E, r;
    if (PRM)
        asm("prmt.b32 %0, %1, %2, 0x5410;" : "=r"(L) : "r"(__float_as_uint(t0)), "r"(__float_as_uint(t1)));
    else
        L = __float_as_uint(t1) * 65536u + __float_as_uint(t0);
    asm("lop3.b32 %0, %1, 0x007F007F, %2, 0xEA;" : "=r"(y2) : "r"(L), "r"(c3f));
    E = L & 0x7F807F80u;
    asm("fma.rn.bf16x2 %0, %1, %2, %3;" : "=r"(r) : "r"(L), "r"(y2), "r"(E));
    return r;
}
#define EXP_MASK 0x4949u
template <int BASE>
__device__ __forceinline__ void exp_half(const float* s, uint32_t* p, uint32_t c3f) {
#pragma unroll
    for (int i = 0; i < 8; i++) {
        if ((EXP_MASK >> (BASE + i)) & 1) p[i] = exp_pair_mufu(s[2 * i], s[2 * i + 1]);
        else if (i & 1) p[i] = exp_pair_poly<1>(s[2 * i], s[2 * i + 1], c3f);
        else p[i] = exp_pair_poly<0>(s[2 * i], s[2 * i + 1], c3f);
    }
}

struct Maps {
    CUtensorMap x;
    CUtensorMap wq[2];
    CUtensorMap wkv[4];
    CUtensorMap o;
    CUtensorMap wo[2];
};
#define A_STAGES 4
#define A_STAGE_BYTES 40960
#define CHUNK_BYTES 20480
#define SM_Q 163840
#define C_STAGES 4
#define C_STAGE_BYTES 49152
#define SM_XCH 196608
#define SM_BAR 212992
#define BAR_AF (SM_BAR)
#define BAR_AE (SM_BAR + 32)
#define BAR_KV (SM_BAR + 64)
#define BAR_CF (SM_BAR + 128)
#define BAR_CE (SM_BAR + 192)
#define SM_MISC (SM_BAR + 256)
#define SMEM_TOTAL (SM_BAR + 512 + 1024)

__device__ __forceinline__ void spin_until(const unsigned int* ctr, unsigned int target) {
    unsigned int v;
    for (unsigned int it = 0; it < (1u << 26); it++) {
        asm volatile("ld.acquire.gpu.global.u32 %0, [%1];" : "=r"(v) : "l"(ctr) : "memory");
        if (v >= target) return;
    }
    __trap();
}
__device__ __forceinline__ void signal(unsigned int* ctr) {
    __threadfence();
    asm volatile("red.release.gpu.global.add.u32 [%0], 1;" ::"l"(ctr) : "memory");
}

__device__ __forceinline__ void attn_tile_slow(const uint32_t* qq, uint64_t kd0, uint64_t vd0, float* o, float* s, uint32_t* p) {
    float m0 = -INFINITY, m1 = -INFINITY;
#pragma unroll 1
    for (int ch = 0; ch < 32; ch++) {
        wg_fence();
        qk_n64(s, qq, kd0 + (uint64_t)((ch >> 2) * 1280 + (ch & 3) * 64));
        wg_commit();
        wg_wait<0>();
        fence_regs<32>(s);
#pragma unroll
        for (int j = 0; j < 8; j++) {
            m0 = fmaxf(m0, fmaxf(s[4 * j], s[4 * j + 1]));
            m1 = fmaxf(m1, fmaxf(s[4 * j + 2], s[4 * j + 3]));
        }
    }
    m0 = fmaxf(m0, __shfl_xor_sync(0xffffffffu, m0, 1));
    m1 = fmaxf(m1, __shfl_xor_sync(0xffffffffu, m1, 1));
    m0 = fmaxf(m0, __shfl_xor_sync(0xffffffffu, m0, 2));
    m1 = fmaxf(m1, __shfl_xor_sync(0xffffffffu, m1, 2));
#pragma unroll 1
    for (int ch = 0; ch < 32; ch++) {
        wg_fence();
        qk_n64(s, qq, kd0 + (uint64_t)((ch >> 2) * 1280 + (ch & 3) * 64));
        wg_commit();
        wg_wait<0>();
        fence_regs<32>(s);
#pragma unroll
        for (int j = 0; j < 8; j++) {
            p[2 * j] = exp_pair_mufu(s[4 * j] - m0, s[4 * j + 1] - m0);
            p[2 * j + 1] = exp_pair_mufu(s[4 * j + 2] - m1, s[4 * j + 3] - m1);
        }
        wg_fence();
#pragma unroll
        for (int j = 0; j < 4; j++) pv_n24(o, p + 4 * j, vd0 + (uint64_t)((ch >> 2) * 1280 + (ch & 3) * 64 + 16 * j));
        wg_commit();
        wg_wait<0>();
        fence_regs<12>(o);
    }
}

__global__ void __launch_bounds__(512, 1) fused_kernel(const __grid_constant__ Maps maps, const bf16* __restrict__ x, const bf16* __restrict__ gate_w,
                                                        const bf16* __restrict__ wqa, const bf16* __restrict__ wqb, const bf16* __restrict__ woa,
                                                        const bf16* __restrict__ wob, bf16* __restrict__ out) {
    extern __shared__ unsigned char smem_raw[];
    const uint32_t sb = (smem_u32(smem_raw) + 1023) & ~1023u;
    unsigned char* smem = smem_raw + (sb - smem_u32(smem_raw));
    const int tid = threadIdx.x;
    const int wg = __shfl_sync(0xffffffffu, tid >> 7, 0);
    const int mb = blockIdx.x >> 3, nb = blockIdx.x & 7;
    const int br = nb >> 2;
    ts_min(0); ts_max(16);
    if (tid == 0) {
        for (int i = 0; i < 4; i++) {
            mbar_init(sb + BAR_AF + i * 8, 1);
            mbar_init(sb + BAR_AE + i * 8, 8);
        }
        for (int i = 0; i < 8; i++) {
            mbar_init(sb + BAR_KV + i * 8, 1);
            mbar_init(sb + BAR_CF + i * 8, 1);
            mbar_init(sb + BAR_CE + i * 8, 4);
        }
        *(unsigned int*)(smem + SM_MISC) = 0u;
        asm volatile("fence.mbarrier_init.release.cluster;" ::: "memory");
    }
    if (tid == 384) {
        l2_prefetch(x + (size_t)blockIdx.x * 8192, 16384);
        l2_prefetch(wqa + (size_t)blockIdx.x * 2048, 4096);
        l2_prefetch(wqb + (size_t)blockIdx.x * 2048, 4096);
    }
    __syncthreads();

    if (wg < 2) {
        const int warp = tid >> 5, lane = tid & 31;
        float acc[68];
#pragma unroll
        for (int i = 0; i < 68; i++) acc[i] = 0.f;
        fence_regs<68>(acc);
#pragma unroll
        for (int kb = 0; kb < 8; kb++) {
            const int st = kb % A_STAGES;
            const uint32_t s0 = sb + st * A_STAGE_BYTES;
            mbar_wait_u(sb + BAR_AF + st * 8, kb >= A_STAGES ? 1 : 0);
            if (kb == 0) { ts_min(12); ts_max(28); }
            const uint64_t ad = make_desc(s0 + wg * 8192, 16, 1024, 1);
            const uint64_t bd = make_desc(s0 + 16384, 8192, 1024, 1);
            wg_fence();
#pragma unroll
            for (int kk = 0; kk < 4; kk++) mma_n136_ss(acc, ad + kk * 2, bd + kk * 128);
            wg_commit();
            if (kb >= 1 && kb <= 8 - A_STAGES) {
                wg_wait<1>();
                if (lane == 0) mbar_arrive(sb + BAR_AE + (kb - 1) * 8);
            }
        }
        wg_wait<0>();
        fence_regs<68>(acc);
        ts_min(1); ts_max(17);
        const int r = lane >> 2, c = lane & 3;
        const int lrow = (warp & 3) * 16 + r;
        const int row = mb * 128 + wg * 64 + lrow;
        const uint32_t k0 = pack_bf16(acc[64], acc[65]), k1 = pack_bf16(acc[66], acc[67]);
        bf16* kvp = g_KV + (size_t)br * 65536 + (row >> 8) * 8192 + (nb & 3) * 2048 + (row & 255) * 8 + 2 * c;
        *(uint32_t*)kvp = k0;
        *(uint32_t*)(kvp + 64) = k1;
        float m;
        if (((nb >> 1) & 1) == 0) {
            float n0 = bf_lo(k0) * bf_lo(k0) + bf_hi(k0) * bf_hi(k0);
            float n1 = bf_lo(k1) * bf_lo(k1) + bf_hi(k1) * bf_hi(k1);
            n0 += __shfl_xor_sync(0xffffffffu, n0, 1);
            n1 += __shfl_xor_sync(0xffffffffu, n1, 1);
            n0 += __shfl_xor_sync(0xffffffffu, n0, 2);
            n1 += __shfl_xor_sync(0xffffffffu, n1, 2);
            m = __uint_as_float(max(__float_as_uint(n0), __float_as_uint(n1)));
        } else {
            uint32_t u = max(max((k0 << 16) & 0x7FFFFFFFu, k0 & 0x7FFF0000u), max((k1 << 16) & 0x7FFFFFFFu, k1 & 0x7FFF0000u));
            m = __uint_as_float(u);
        }
        const unsigned int mu = __reduce_max_sync(0xffffffffu, __float_as_uint(m));
        if (lane == 0) atomicMax((unsigned int*)(smem + SM_MISC), mu);
        fence_async();
        asm volatile("bar.sync 1, 256;" ::: "memory");
        if (tid == 0) {
            g_nrm[blockIdx.x] = *(volatile float*)(smem + SM_MISC);
            signal(&g_ctr[br]);
        }
        const float qs = 0.25f * 1.4426950408889634f;
        unsigned char* qp = smem + SM_Q + wg * 2048 + lrow * 32 + c * 8;
#pragma unroll
        for (int h = 0; h < 8; h++) {
            const float* a = acc + h * 8;
            *(uint2*)(qp + h * 4096) = make_uint2(pack_bf16(a[0] * qs, a[1] * qs), pack_bf16(a[4] * qs, a[5] * qs));
            *(uint2*)(qp + h * 4096 + 256) = make_uint2(pack_bf16(a[2] * qs, a[3] * qs), pack_bf16(a[6] * qs, a[7] * qs));
        }
#pragma unroll
        for (int i = 0; i < 8; i++) *(uint4*)(smem + i * CHUNK_BYTES + 16384 + tid * 16) = make_uint4(0x00003F80u, 0, 0, 0);
        asm volatile("fence.proxy.async.shared::cta;" ::: "memory");
        ts_min(2); ts_max(18);
    } else if (wg == 2) {
        if (tid == 256) {
            for (int kb = 0; kb < 8; kb++) {
                const int st = kb % A_STAGES;
                if (kb >= A_STAGES) mbar_wait(sb + BAR_AE + st * 8, 0);
                const uint32_t s0 = sb + st * A_STAGE_BYTES, fb = sb + BAR_AF + st * 8;
                mbar_expect_tx(fb, A_STAGE_BYTES);
                tma_2d(s0, &maps.x, kb * 64, mb * 128, fb);
                tma_2d(s0 + 16384, &maps.wq[br], (nb & 3) * 128, kb * 64, fb);
                tma_2d(s0 + 24576, &maps.wq[br], (nb & 3) * 128 + 64, kb * 64, fb);
                tma_2d(s0 + 32768, &maps.wkv[nb >> 1], (nb & 1) * 8, kb * 64, fb);
            }
            l2_prefetch(woa + (size_t)blockIdx.x * 2048, 4096);
            l2_prefetch(wob + (size_t)blockIdx.x * 2048, 4096);
            spin_until(&g_ctr[br], 64);
            fence_async();
            ts_min(4); ts_max(20);
            const unsigned char* src = (const unsigned char*)g_KV + (size_t)br * 131072;
            for (int g = 0; g < 8; g++) {
                mbar_expect_tx(sb + BAR_KV + g * 8, 16384);
                bulk_g2s(sb + g * CHUNK_BYTES, src + g * 16384, 16384, sb + BAR_KV + g * 8);
            }
            unsigned int h0 = 0, h1 = 0, hv = 0;
            for (int i = 0; i < 16; i++) {
                const uint4 v = __ldcg((const uint4*)(g_nrm + i * 8 + br * 4));
                h0 = max(h0, v.x);
                h1 = max(h1, v.y);
                hv = max(hv, max(v.z, v.w));
            }
            float kmax2 = __uint_as_float(h0) + __uint_as_float(h1);
            if (!(__uint_as_float(hv) <= 1.0e15f)) kmax2 = __uint_as_float(0x7FC00000u);
            *(volatile float*)(smem + SM_MISC + 4) = kmax2;
        }
        __syncwarp();
    } else {
        const int lane = tid & 31, w = (tid >> 5) & 3;
        const uint4* gw = (const uint4*)(gate_w + lane * 16);
        const uint4 w0 = __ldg(gw), w1 = __ldg(gw + 1);
        const uint32_t wv[8] = {w0.x, w0.y, w0.z, w0.w, w1.x, w1.y, w1.z, w1.w};
        uint4 xa[4][2];
#pragma unroll
        for (int rr = 0; rr < 4; rr++) {
            const uint4* xp = (const uint4*)(x + (size_t)(blockIdx.x * 16 + w * 4 + rr) * DM + lane * 16);
            xa[rr][0] = __ldg(xp);
            xa[rr][1] = __ldg(xp + 1);
        }
#pragma unroll
        for (int rr = 0; rr < 4; rr++) {
            const uint32_t xv[8] = {xa[rr][0].x, xa[rr][0].y, xa[rr][0].z, xa[rr][0].w, xa[rr][1].x, xa[rr][1].y, xa[rr][1].z, xa[rr][1].w};
            float sum = 0.f;
#pragma unroll
            for (int i = 0; i < 8; i++) {
                sum += bf_round(bf_lo(xv[i]) * bf_lo(wv[i]));
                sum += bf_round(bf_hi(xv[i]) * bf_hi(wv[i]));
            }
#pragma unroll
            for (int o = 16; o > 0; o >>= 1) sum += __shfl_xor_sync(0xffffffffu, sum, o);
            if (lane == 0) {
                sum = bf_round(sum);
                g_gate[blockIdx.x * 16 + w * 4 + rr] = bf_round(1.f / (1.f + __expf(-sum)));
            }
        }
    }
    __syncthreads();

    {
        uint32_t c3f = 0x3F003F00u;
        asm volatile("" : "+r"(c3f));
        const uint64_t kd0 = make_desc(sb, 4096, 128, 0);
        const uint64_t vd0 = make_desc(sb + 8192, 128, 4096, 0);
#pragma unroll 1
        for (int t = 0; t < 4; t++) {
            uint32_t q[4];
            uint32_t any_unsafe;
            {
                const unsigned char* qp = smem + SM_Q + (wg * 4 + t) * 2048 + ((tid >> 5) & 3) * 512 + (tid & 31) * 8;
                const uint2 a = *(const uint2*)qp, b = *(const uint2*)(qp + 256);
                q[0] = a.x; q[2] = a.y; q[1] = b.x; q[3] = b.y;
                float n0 = bf_lo(q[0]) * bf_lo(q[0]) + bf_hi(q[0]) * bf_hi(q[0]) + bf_lo(q[2]) * bf_lo(q[2]) + bf_hi(q[2]) * bf_hi(q[2]);
                float n1 = bf_lo(q[1]) * bf_lo(q[1]) + bf_hi(q[1]) * bf_hi(q[1]) + bf_lo(q[3]) * bf_lo(q[3]) + bf_hi(q[3]) * bf_hi(q[3]);
                n0 += __shfl_xor_sync(0xffffffffu, n0, 1);
                n1 += __shfl_xor_sync(0xffffffffu, n1, 1);
                n0 += __shfl_xor_sync(0xffffffffu, n0, 2);
                n1 += __shfl_xor_sync(0xffffffffu, n1, 2);
                const float kmax2 = *(volatile float*)(smem + SM_MISC + 4);
                const bool unsafe = !(n0 * kmax2 <= 3600.f) || !(n1 * kmax2 <= 3600.f);
                asm volatile(
                    "{\n.reg .pred p, q;\nsetp.ne.u32 q, %1, 0;\nbar.red.or.pred p, %2, 128, q;\nselp.u32 %0, 1, 0, p;\n}"
                    : "=r"(any_unsafe) : "r"((uint32_t)unsafe), "r"(wg + 1) : "memory");
            }
            float o[12];
            float s0[32], s1[32];
            uint32_t p[16];
#pragma unroll
            for (int i = 0; i < 12; i++) o[i] = 0.f;
            fence_regs<12>(o);
            if (__any_sync(0xffffffffu, any_unsafe)) {
                for (int g = 0; g < 8; g++) mbar_wait_u(sb + BAR_KV + g * 8, 0);
                attn_tile_slow(q, kd0, vd0, o, s0, p);
            } else {
                mbar_wait_u(sb + BAR_KV, 0);
                if (t == 0) { ts_min(5); ts_max(21); }
                wg_fence();
                qk_n64(s0, q, kd0);
                wg_commit();
                wg_wait<0>();
                fence_regs<32>(s0);
                uint64_t kd = kd0, vd = vd0;
#pragma unroll 1
                for (uint32_t it = 0; it < 16; it++) {
                    wg_fence();
                    qk_n64(s1, q, kd + 64);
                    wg_commit();
                    exp_half<0>(s0, p, c3f);
                    wg_fence();
                    pv_n24(o, p, vd);
                    pv_n24(o, p + 4, vd + 16);
                    wg_commit();
                    wg_wait<2>();
                    exp_half<8>(s0 + 16, p + 8, c3f);
                    wg_fence();
                    pv_n24(o, p + 8, vd + 32);
                    pv_n24(o, p + 12, vd + 48);
                    wg_commit();
                    wg_wait<1>();
                    fence_regs<32>(s1);
                    if (it & 1) mbar_wait_u(sb + BAR_KV + (((it + 1) >> 1) & 7) * 8, 0);
                    kd = (it == 15) ? kd0 : kd + ((it & 1) ? 1152 : 128);
                    wg_fence();
                    qk_n64(s0, q, kd);
                    wg_commit();
                    exp_half<0>(s1, p, c3f);
                    wg_fence();
                    pv_n24(o, p, vd + 64);
                    pv_n24(o, p + 4, vd + 80);
                    wg_commit();
                    wg_wait<2>();
                    exp_half<8>(s1 + 16, p + 8, c3f);
                    wg_fence();
                    pv_n24(o, p + 8, vd + 96);
                    pv_n24(o, p + 12, vd + 112);
                    wg_commit();
                    wg_wait<1>();
                    fence_regs<32>(s0);
                    vd += (it & 1) ? 1152 : 128;
                }
                wg_wait<0>();
                fence_regs<12>(o);
            }
            {
                int tid2;
                asm volatile("mov.u32 %0, %%tid.x;" : "=r"(tid2));
                const int lane = tid2 & 31;
                const float l0 = __shfl_sync(0xffffffffu, o[8], lane & ~3);
                const float l1 = __shfl_sync(0xffffffffu, o[10], lane & ~3);
                const float i0 = 1.f / l0, i1 = 1.f / l1;
                const int tile = wg * 4 + t;
                const uint32_t row = (uint32_t)(br * SEQ + mb * 128 + (tile & 1) * 64 + ((tid2 >> 5) & 3) * 16 + (lane >> 2));
                bf16* op = g_O + row * DM + ((nb & 3) * 8 + (tile >> 1)) * 16 + (lane & 3) * 2;
                *(uint32_t*)(op) = pack_bf16(o[0] * i0, o[1] * i0);
                *(uint32_t*)(op + 8 * DM) = pack_bf16(o[2] * i1, o[3] * i1);
                *(uint32_t*)(op + 8) = pack_bf16(o[4] * i0, o[5] * i0);
                *(uint32_t*)(op + 8 * DM + 8) = pack_bf16(o[6] * i1, o[7] * i1);
            }
        }
    }
    fence_async();
    __syncthreads();
    ts_min(6); ts_max(22);

    const int orow0 = mb * 128 + (nb >> 2) * 64, ocol0 = (nb & 3) * 128;
    if (wg == 2) {
        if (tid == 256) {
            signal(&g_ctr[2 + mb]);
            for (int i = 0; i < 2 * C_STAGES; i++) {
                const int kb = i >> 1, b = i & 1;
                const uint32_t s0 = sb + kb * C_STAGE_BYTES + b * 24576;
                mbar_expect_tx(sb + BAR_CF + i * 8, 24576);
                tma_2d(s0 + 8192, &maps.wo[b], ocol0, kb * 64, sb + BAR_CF + i * 8);
                tma_2d(s0 + 16384, &maps.wo[b], ocol0 + 64, kb * 64, sb + BAR_CF + i * 8);
            }
            spin_until(&g_ctr[2 + mb], 8);
            fence_async();
            for (int i = 0; i < 2 * C_STAGES; i++) {
                const int kb = i >> 1, b = i & 1;
                tma_2d(sb + kb * C_STAGE_BYTES + b * 24576, &maps.o, kb * 64, b * SEQ + orow0, sb + BAR_CF + i * 8);
            }
            for (int i = 0; i < 2 * C_STAGES; i++) {
                const int kb = C_STAGES + (i >> 1), b = i & 1;
                const uint32_t s0 = sb + (i >> 1) * C_STAGE_BYTES + b * 24576;
                mbar_wait(sb + BAR_CE + i * 8, 0);
                mbar_expect_tx(sb + BAR_CF + i * 8, 24576);
                tma_2d(s0, &maps.o, kb * 64, b * SEQ + orow0, sb + BAR_CF + i * 8);
                tma_2d(s0 + 8192, &maps.wo[b], ocol0, kb * 64, sb + BAR_CF + i * 8);
                tma_2d(s0 + 16384, &maps.wo[b], ocol0 + 64, kb * 64, sb + BAR_CF + i * 8);
            }
            __threadfence();
            if (atomicAdd(&g_ctr[18], 1u) == 127u) {
                for (int i = 0; i < 19; i++) g_ctr[i] = 0u;
            }
        }
    } else if (wg < 2) {
        const int warp = tid >> 5, lane = tid & 31;
        float acc[64];
#pragma unroll
        for (int i = 0; i < 64; i++) acc[i] = 0.f;
        fence_regs<64>(acc);
        const int r = lane >> 2, c = lane & 3;
        const int lrow = (warp & 3) * 16 + r;
        float g0 = 0.f, g1 = 0.f;
#pragma unroll
        for (int kb = 0; kb < 8; kb++) {
            const int st = kb % C_STAGES;
            const uint32_t s0 = sb + st * C_STAGE_BYTES + wg * 24576;
            mbar_wait_u(sb + BAR_CF + (st * 2 + wg) * 8, kb >= C_STAGES ? 1 : 0);
            if (kb == 0) {
                ts_min(8); ts_max(24);
                g0 = __ldcg(g_gate + orow0 + lrow);
                g1 = __ldcg(g_gate + orow0 + lrow + 8);
            }
            const uint64_t ad = make_desc(s0, 16, 1024, 1);
            const uint64_t bd = make_desc(s0 + 8192, 8192, 1024, 1);
            wg_fence();
#pragma unroll
            for (int kk = 0; kk < 4; kk++) mma_n128_ss(acc, ad + kk * 2, bd + kk * 128);
            wg_commit();
            if (kb >= 1 && kb <= C_STAGES) {
                wg_wait<1>();
                if (lane == 0) mbar_arrive(sb + BAR_CE + ((kb - 1) * 2 + wg) * 8);
            }
        }
        wg_wait<0>();
        fence_regs<64>(acc);
        ts_min(9); ts_max(25);
        if (wg) { g0 = bf_round(1.f - g0); g1 = bf_round(1.f - g1); }
        uint32_t t[32];
#pragma unroll
        for (int j = 0; j < 16; j++) {
            t[2 * j] = pack_bf16(g0 * bf_round(acc[4 * j]), g0 * bf_round(acc[4 * j + 1]));
            t[2 * j + 1] = pack_bf16(g1 * bf_round(acc[4 * j + 2]), g1 * bf_round(acc[4 * j + 3]));
        }
        uint32_t* xch = (uint32_t*)(smem + SM_XCH);
        const int lt = tid & 127;
#pragma unroll
        for (int j = 0; j < 16; j++) xch[(wg * 16 + j) * 128 + lt] = wg ? t[j] : t[16 + j];
        asm volatile("bar.sync 1, 256;" ::: "memory");
        unsigned char* ot = smem + wg * 16384;
#pragma unroll
        for (int j = 0; j < 16; j++) {
            const uint32_t mine = wg ? t[16 + j] : t[j];
            const uint32_t other = xch[((wg ^ 1) * 16 + j) * 128 + lt];
            const uint32_t v = pack_bf16(bf_lo(mine) + bf_lo(other), bf_hi(mine) + bf_hi(other));
            *(uint32_t*)(ot + (lrow + (j & 1) * 8) * 144 + (j >> 1) * 16 + c * 4) = v;
        }
        asm volatile("bar.sync %0, 128;" ::"r"(wg + 2) : "memory");
#pragma unroll
        for (int i = 0; i < 4; i++) {
            const int idx = i * 128 + lt, row = idx >> 3, ch = idx & 7;
            const uint4 v = *(const uint4*)(ot + row * 144 + ch * 16);
            *(uint4*)(out + (size_t)(orow0 + row) * DM + ocol0 + wg * 64 + ch * 8) = v;
        }
        ts_min(10); ts_max(26);
    }
}

typedef CUresult (*EncodeFn)(CUtensorMap*, CUtensorMapDataType, cuuint32_t, void*, const cuuint64_t*, const cuuint64_t*, const cuuint32_t*,
                             const cuuint32_t*, CUtensorMapInterleave, CUtensorMapSwizzle, CUtensorMapL2promotion, CUtensorMapFloatOOBfill);

static void encode_2d(EncodeFn fn, CUtensorMap* m, const void* ptr, uint64_t inner, uint64_t outer, uint32_t box_inner, uint32_t box_outer) {
    cuuint64_t dims[2] = {inner, outer};
    cuuint64_t strides[1] = {inner * 2};
    cuuint32_t box[2] = {box_inner, box_outer};
    cuuint32_t es[2] = {1, 1};
    fn(m, CU_TENSOR_MAP_DATA_TYPE_BFLOAT16, 2, (void*)ptr, dims, strides, box, es, CU_TENSOR_MAP_INTERLEAVE_NONE, CU_TENSOR_MAP_SWIZZLE_128B,
       CU_TENSOR_MAP_L2_PROMOTION_L2_256B, CU_TENSOR_MAP_FLOAT_OOB_FILL_NONE);
}

extern "C" void kernel_launch(void* const* d_in, const int* in_sizes, int n_in, void* d_out, int out_size) {
    (void)in_sizes; (void)n_in; (void)out_size;
    static Maps m;
    static const void* cached[11] = {0};
    static bool attr_done = false;
    bool same = true;
    for (int i = 0; i < 11; i++) same = same && (cached[i] == d_in[i]);
    if (!same || !attr_done) {
        void* fnp = nullptr;
        cudaDriverEntryPointQueryResult qr;
        cudaGetDriverEntryPoint("cuTensorMapEncodeTiled", &fnp, cudaEnableDefault, &qr);
        EncodeFn fn = (EncodeFn)fnp;
        void* po = nullptr;
        cudaGetSymbolAddress(&po, g_O);
        encode_2d(fn, &m.x, d_in[0], DM, SEQ, 64, 128);
        encode_2d(fn, &m.wq[0], d_in[1], DM, DM, 64, 64);
        encode_2d(fn, &m.wq[1], d_in[6], DM, DM, 64, 64);
        encode_2d(fn, &m.wkv[0], d_in[2], 16, DM, 64, 64);
        encode_2d(fn, &m.wkv[1], d_in[3], 16, DM, 64, 64);
        encode_2d(fn, &m.wkv[2], d_in[7], 16, DM, 64, 64);
        encode_2d(fn, &m.wkv[3], d_in[8], 16, DM, 64, 64);
        encode_2d(fn, &m.o, po, DM, 2 * SEQ, 64, 64);
        encode_2d(fn, &m.wo[0], d_in[4], DM, DM, 64, 64);
        encode_2d(fn, &m.wo[1], d_in[9], DM, DM, 64, 64);
        cudaFuncSetAttribute(fused_kernel, cudaFuncAttributeMaxDynamicSharedMemorySize, SMEM_TOTAL);
        for (int i = 0; i < 11; i++) cached[i] = d_in[i];
        attr_done = true;
    }
    cudaLaunchAttribute at[1];
    at[0].id = cudaLaunchAttributeCooperative;
    at[0].val.cooperative = 1;
    cudaLaunchConfig_t cfg = {};
    cfg.stream = cudaStreamPerThread;
    cfg.attrs = at;
    cfg.numAttrs = 1;
    cfg.gridDim = dim3(128);
    cfg.blockDim = dim3(512);
    cfg.dynamicSmemBytes = SMEM_TOTAL;
    cudaLaunchKernelEx(&cfg, fused_kernel, m, (const bf16*)d_in[0], (const bf16*)d_in[10], (const bf16*)d_in[1], (const bf16*)d_in[6],
                       (const bf16*)d_in[4], (const bf16*)d_in[9], (bf16*)d_out);
}
```

```cpp
#include <cuda_runtime.h>
#include <cuda_bf16.h>
#include <cuda.h>
#include <stdint.h>

typedef __nv_bfloat16 bf16;

#define SEQ 2048
#define DM 512
#define ROWS 65536

__device__ __align__(1024) bf16 g_KV[2 * 4 * SEQ * 8];
__device__ __align__(1024) bf16 g_O[2 * ROWS * 16];
__device__ float g_gate[SEQ];
__device__ __align__(16) float g_nrm[128];
__device__ unsigned int g_ctr[32];

#define ts_min(i)
#define ts_max(i)
__device__ __forceinline__ uint32_t smem_u32(const void* p) { return (uint32_t)__cvta_generic_to_shared(p); }
__device__ __forceinline__ uint64_t make_desc(uint32_t saddr, uint32_t lbo, uint32_t sbo, uint32_t swz) {
    uint64_t d = 0;
    d |= (uint64_t)((saddr & 0x3FFFF) >> 4);
    d |= (uint64_t)((lbo & 0x3FFFF) >> 4) << 16;
    d |= (uint64_t)((sbo & 0x3FFFF) >> 4) << 32;
    d |= (uint64_t)swz << 62;
    return d;
}
__device__ __forceinline__ void wg_fence() { asm volatile("wgmma.fence.sync.aligned;" ::: "memory"); }
__device__ __forceinline__ void wg_commit() { asm volatile("wgmma.commit_group.sync.aligned;" ::: "memory"); }
template <int N> __device__ __forceinline__ void wg_wait() { asm volatile("wgmma.wait_group.sync.aligned %0;" ::"n"(N) : "memory"); }
template <int N> __device__ __forceinline__ void fence_regs(float* d) {
#pragma unroll
    for (int i = 0; i < N; i++) asm volatile("" : "+f"(d[i])::"memory");
}
__device__ __forceinline__ void mbar_init(uint32_t bar, uint32_t cnt) { asm volatile("mbarrier.init.shared::cta.b64 [%0], %1;" ::"r"(bar), "r"(cnt)); }
__device__ __forceinline__ void mbar_expect_tx(uint32_t bar, uint32_t bytes) {
    asm volatile("mbarrier.arrive.expect_tx.shared::cta.b64 _, [%0], %1;" ::"r"(bar), "r"(bytes) : "memory");
}
__device__ __forceinline__ void mbar_arrive(uint32_t bar) { asm volatile("mbarrier.arrive.shared::cta.b64 _, [%0];" ::"r"(bar) : "memory"); }
__device__ __forceinline__ void mbar_wait(uint32_t bar, uint32_t parity) {
    asm volatile(
        "{\n.reg .pred p;\n"
        "WAIT_LOOP:\n"
        "mbarrier.try_wait.parity.shared::cta.b64 p, [%0], %1;\n"
        "@p bra DONE;\n"
        "bra WAIT_LOOP;\n"
        "DONE:\n}" ::"r"(bar), "r"(parity) : "memory");
}
__device__ __forceinline__ void mbar_wait_u(uint32_t bar, uint32_t parity) {
    uint32_t ok;
    do {
        asm volatile(
            "{\n.reg .pred p;\nmbarrier.try_wait.parity.shared::cta.b64 p, [%1], %2;\nselp.u32 %0, 1, 0, p;\n}"
            : "=r"(ok) : "r"(bar), "r"(parity) : "memory");
    } while (!__all_sync(0xffffffffu, ok));
}
__device__ __forceinline__ void bulk_g2s(uint32_t dst, const void* src, uint32_t bytes, uint32_t bar) {
    asm volatile("cp.async.bulk.shared::cluster.global.mbarrier::complete_tx::bytes [%0], [%1], %2, [%3];" ::"r"(dst), "l"(src), "r"(bytes), "r"(bar) : "memory");
}
__device__ __forceinline__ void tma_2d(uint32_t dst, const CUtensorMap* map, int c0, int c1, uint32_t bar) {
    asm volatile("cp.async.bulk.tensor.2d.shared::cluster.global.mbarrier::complete_tx::bytes [%0], [%1, {%3, %4}], [%2];" ::"r"(dst), "l"(map), "r"(bar), "r"(c0), "r"(c1) : "memory");
}
__device__ __forceinline__ void l2_prefetch(const void* p, uint32_t bytes) {
    asm volatile("cp.async.bulk.prefetch.L2.global [%0], %1;" ::"l"(p), "r"(bytes) : "memory");
}
__device__ __forceinline__ void pdl_launch() { asm volatile("griddepcontrol.launch_dependents;" ::: "memory"); }
__device__ __forceinline__ void pdl_wait() { asm volatile("griddepcontrol.wait;" ::: "memory"); }
__device__ __forceinline__ void fence_async() { asm volatile("fence.proxy.async;" ::: "memory"); }
__device__ __forceinline__ uint32_t pack_bf16(float lo, float hi) {
    uint32_t r;
    asm("cvt.rn.bf16x2.f32 %0, %1, %2;" : "=r"(r) : "f"(hi), "f"(lo));
    return r;
}
__device__ __forceinline__ float bf_lo(uint32_t u) { return __uint_as_float(u << 16); }
__device__ __forceinline__ float bf_hi(uint32_t u) { return __uint_as_float(u & 0xFFFF0000u); }
__device__ __forceinline__ float bf_round(float x) { return __bfloat162float(__float2bfloat16_rn(x)); }

#define A8(b) "+f"(d[b + 0]), "+f"(d[b + 1]), "+f"(d[b + 2]), "+f"(d[b + 3]), "+f"(d[b + 4]), "+f"(d[b + 5]), "+f"(d[b + 6]), "+f"(d[b + 7])
#define W8(b) "=f"(d[b + 0]), "=f"(d[b + 1]), "=f"(d[b + 2]), "=f"(d[b + 3]), "=f"(d[b + 4]), "=f"(d[b + 5]), "=f"(d[b + 6]), "=f"(d[b + 7])

__device__ __forceinline__ void mma_n136_ss(float* d, uint64_t ad, uint64_t bd) {
    asm volatile(
        "wgmma.mma_async.sync.aligned.m64n136k16.f32.bf16.bf16 "
        "{%0,%1,%2,%3,%4,%5,%6,%7,%8,%9,%10,%11,%12,%13,%14,%15,%16,%17,%18,%19,%20,%21,%22,%23,%24,%25,%26,%27,%28,%29,%30,%31,"
        "%32,%33,%34,%35,%36,%37,%38,%39,%40,%41,%42,%43,%44,%45,%46,%47,%48,%49,%50,%51,%52,%53,%54,%55,%56,%57,%58,%59,%60,%61,%62,%63,"
        "%64,%65,%66,%67}, %68, %69, 1, 1, 1, 0, 1;"
        : A8(0), A8(8), A8(16), A8(24), A8(32), A8(40), A8(48), A8(56), "+f"(d[64]), "+f"(d[65]), "+f"(d[66]), "+f"(d[67])
        : "l"(ad), "l"(bd));
}
__device__ __forceinline__ void mma_n128_ss(float* d, uint64_t ad, uint64_t bd) {
    asm volatile(
        "wgmma.mma_async.sync.aligned.m64n128k16.f32.bf16.bf16 "
        "{%0,%1,%2,%3,%4,%5,%6,%7,%8,%9,%10,%11,%12,%13,%14,%15,%16,%17,%18,%19,%20,%21,%22,%23,%24,%25,%26,%27,%28,%29,%30,%31,"
        "%32,%33,%34,%35,%36,%37,%38,%39,%40,%41,%42,%43,%44,%45,%46,%47,%48,%49,%50,%51,%52,%53,%54,%55,%56,%57,%58,%59,%60,%61,%62,%63}, "
        "%64, %65, 1, 1, 1, 0, 1;"
        : A8(0), A8(8), A8(16), A8(24), A8(32), A8(40), A8(48), A8(56)
        : "l"(ad), "l"(bd));
}
__device__ __forceinline__ void qk_n64(float* d, const uint32_t* a, uint64_t bd) {
    asm volatile(
        "wgmma.mma_async.sync.aligned.m64n64k16.f32.bf16.bf16 "
        "{%0,%1,%2,%3,%4,%5,%6,%7,%8,%9,%10,%11,%12,%13,%14,%15,%16,%17,%18,%19,%20,%21,%22,%23,%24,%25,%26,%27,%28,%29,%30,%31}, "
        "{%32,%33,%34,%35}, %36, 0, 1, 1, 0;"
        : W8(0), W8(8), W8(16), W8(24)
        : "r"(a[0]), "r"(a[1]), "r"(a[2]), "r"(a[3]), "l"(bd));
}
__device__ __forceinline__ void pv_n24(float* d, const uint32_t* a, uint64_t bd) {
    asm volatile(
        "wgmma.mma_async.sync.aligned.m64n24k16.f32.bf16.bf16 {%0,%1,%2,%3,%4,%5,%6,%7,%8,%9,%10,%11}, {%12,%13,%14,%15}, %16, 1, 1, 1, 1;"
        : A8(0), "+f"(d[8]), "+f"(d[9]), "+f"(d[10]), "+f"(d[11])
        : "r"(a[0]), "r"(a[1]), "r"(a[2]), "r"(a[3]), "l"(bd));
}

__device__ __forceinline__ float ex2(float x) {
    float e;
    asm("ex2.approx.ftz.f32 %0, %1;" : "=f"(e) : "f"(x));
    return e;
}
__device__ __forceinline__ uint32_t exp_pair_mufu(float x0, float x1) { return pack_bf16(ex2(x0), ex2(x1)); }

#define MAGIC0 (98304.0f + 127.0f - 75.0f / 128.0f)
#define MAGIC1 (98304.0f + 127.0f - 75.0f / 128.0f - 143.5f)
template <int PRM>
__device__ __forceinline__ uint32_t exp_pair_poly(float x0, float x1, uint32_t c3f) {
    float t0 = x0 + MAGIC0;
    float t1 = x1 + (PRM ? MAGIC0 : MAGIC1);
    uint32_t L, y2, E, r;
    if (PRM)
        asm("prmt.b32 %0, %1, %2, 0x5410;" : "=r"(L) : "r"(__float_as_uint(t0)), "r"(__float_as_uint(t1)));
    else
        L = __float_as_uint(t1) * 65536u + __float_as_uint(t0);
    asm("lop3.b32 %0, %1, 0x007F007F, %2, 0xEA;" : "=r"(y2) : "r"(L), "r"(c3f));
    E = L & 0x7F807F80u;
    asm("fma.rn.bf16x2 %0, %1, %2, %3;" : "=r"(r) : "r"(L), "r"(y2), "r"(E));
    return r;
}
#define EXP_MASK 0x4949u
template <int BASE>
__device__ __forceinline__ void exp_half(const float* s, uint32_t* p, uint32_t c3f) {
#pragma unroll
    for (int i = 0; i < 8; i++) {
        if ((EXP_MASK >> (BASE + i)) & 1) p[i] = exp_pair_mufu(s[2 * i], s[2 * i + 1]);
        else if (i & 1) p[i] = exp_pair_poly<1>(s[2 * i], s[2 * i + 1], c3f);
        else p[i] = exp_pair_poly<0>(s[2 * i], s[2 * i + 1], c3f);
    }
}

struct Maps {
    CUtensorMap x;
    CUtensorMap wq[2];
    CUtensorMap wkv[4];
    CUtensorMap o;
    CUtensorMap wo[2];
};
#define A_STAGES 4
#define A_STAGE_BYTES 40960
#define CHUNK_BYTES 20480
#define SM_Q 163840
#define C_STAGES 4
#define C_STAGE_BYTES 49152
#define SM_XCH 196608
#define SM_BAR 212992
#define BAR_AF (SM_BAR)
#define BAR_AE (SM_BAR + 32)
#define BAR_KV (SM_BAR + 64)
#define BAR_CF (SM_BAR + 128)
#define BAR_CE (SM_BAR + 192)
#define SM_MISC (SM_BAR + 256)
#define SMEM_TOTAL (SM_BAR + 512 + 1024)

__device__ __forceinline__ void spin_until(const unsigned int* ctr, unsigned int target) {
    unsigned int v;
    for (unsigned int it = 0; it < (1u << 26); it++) {
        asm volatile("ld.acquire.gpu.global.u32 %0, [%1];" : "=r"(v) : "l"(ctr) : "memory");
        if (v >= target) return;
    }
    __trap();
}
__device__ __forceinline__ void signal(unsigned int* ctr) {
    asm volatile("red.release.gpu.global.add.u32 [%0], 1;" ::"l"(ctr) : "memory");
}

__device__ __forceinline__ void attn_tile_slow(const uint32_t* qq, uint64_t kd0, uint64_t vd0, float* o, float* s, uint32_t* p) {
    float m0 = -INFINITY, m1 = -INFINITY;
#pragma unroll 1
    for (int ch = 0; ch < 32; ch++) {
        wg_fence();
        qk_n64(s, qq, kd0 + (uint64_t)((ch >> 2) * 1280 + (ch & 3) * 64));
        wg_commit();
        wg_wait<0>();
        fence_regs<32>(s);
#pragma unroll
        for (int j = 0; j < 8; j++) {
            m0 = fmaxf(m0, fmaxf(s[4 * j], s[4 * j + 1]));
            m1 = fmaxf(m1, fmaxf(s[4 * j + 2], s[4 * j + 3]));
        }
    }
    m0 = fmaxf(m0, __shfl_xor_sync(0xffffffffu, m0, 1));
    m1 = fmaxf(m1, __shfl_xor_sync(0xffffffffu, m1, 1));
    m0 = fmaxf(m0, __shfl_xor_sync(0xffffffffu, m0, 2));
    m1 = fmaxf(m1, __shfl_xor_sync(0xffffffffu, m1, 2));
#pragma unroll 1
    for (int ch = 0; ch < 32; ch++) {
        wg_fence();
        qk_n64(s, qq, kd0 + (uint64_t)((ch >> 2) * 1280 + (ch & 3) * 64));
        wg_commit();
        wg_wait<0>();
        fence_regs<32>(s);
#pragma unroll
        for (int j = 0; j < 8; j++) {
            p[2 * j] = exp_pair_mufu(s[4 * j] - m0, s[4 * j + 1] - m0);
            p[2 * j + 1] = exp_pair_mufu(s[4 * j + 2] - m1, s[4 * j + 3] - m1);
        }
        wg_fence();
#pragma unroll
        for (int j = 0; j < 4; j++) pv_n24(o, p + 4 * j, vd0 + (uint64_t)((ch >> 2) * 1280 + (ch & 3) * 64 + 16 * j));
        wg_commit();
        wg_wait<0>();
        fence_regs<12>(o);
    }
}

__global__ void __launch_bounds__(512, 1) fused_kernel(const __grid_constant__ Maps maps, const bf16* __restrict__ x, const bf16* __restrict__ gate_w,
                                                        const bf16* __restrict__ wqa, const bf16* __restrict__ wqb, const bf16* __restrict__ woa,
                                                        const bf16* __restrict__ wob, bf16* __restrict__ out) {
    extern __shared__ unsigned char smem_raw[];
    const uint32_t sb = (smem_u32(smem_raw) + 1023) & ~1023u;
    unsigned char* smem = smem_raw + (sb - smem_u32(smem_raw));
    const int tid = threadIdx.x;
    const int wg = __shfl_sync(0xffffffffu, tid >> 7, 0);
    const int mb = blockIdx.x >> 3, nb = blockIdx.x & 7;
    const int br = nb >> 2;
    ts_min(0); ts_max(16);
    if (tid == 0) {
        for (int i = 0; i < 4; i++) {
            mbar_init(sb + BAR_AF + i * 8, 1);
            mbar_init(sb + BAR_AE + i * 8, 8);
        }
        for (int i = 0; i < 8; i++) {
            mbar_init(sb + BAR_KV + i * 8, 1);
            mbar_init(sb + BAR_CF + i * 8, 1);
            mbar_init(sb + BAR_CE + i * 8, 4);
        }
        *(unsigned int*)(smem + SM_MISC) = 0u;
        asm volatile("fence.mbarrier_init.release.cluster;" ::: "memory");
    }
    if (tid == 384) {
        l2_prefetch(x + (size_t)blockIdx.x * 8192, 16384);
        l2_prefetch(wqa + (size_t)blockIdx.x * 2048, 4096);
        l2_prefetch(wqb + (size_t)blockIdx.x * 2048, 4096);
    }
    __syncthreads();

    if (wg < 2) {
        const int warp = tid >> 5, lane = tid & 31;
        float acc[68];
#pragma unroll
        for (int i = 0; i < 68; i++) acc[i] = 0.f;
        fence_regs<68>(acc);
#pragma unroll
        for (int kb = 0; kb < 8; kb++) {
            const int st = kb % A_STAGES;
            const uint32_t s0 = sb + st * A_STAGE_BYTES;
            mbar_wait_u(sb + BAR_AF + st * 8, kb >= A_STAGES ? 1 : 0);
            if (kb == 0) { ts_min(12); ts_max(28); }
            const uint64_t ad = make_desc(s0 + wg * 8192, 16, 1024, 1);
            const uint64_t bd = make_desc(s0 + 16384, 8192, 1024, 1);
            wg_fence();
#pragma unroll
            for (int kk = 0; kk < 4; kk++) mma_n136_ss(acc, ad + kk * 2, bd + kk * 128);
            wg_commit();
            if (kb >= 1 && kb <= 8 - A_STAGES) {
                wg_wait<1>();
                if (lane == 0) mbar_arrive(sb + BAR_AE + (kb - 1) * 8);
            }
        }
        wg_wait<0>();
        fence_regs<68>(acc);
        ts_min(1); ts_max(17);
        const int r = lane >> 2, c = lane & 3;
        const int lrow = (warp & 3) * 16 + r;
        const int row = mb * 128 + wg * 64 + lrow;
        const uint32_t k0 = pack_bf16(acc[64], acc[65]), k1 = pack_bf16(acc[66], acc[67]);
        bf16* kvp = g_KV + (size_t)br * 65536 + (row >> 8) * 8192 + (nb & 3) * 2048 + (row & 255) * 8 + 2 * c;
        *(uint32_t*)kvp = k0;
        *(uint32_t*)(kvp + 64) = k1;
        float m;
        if (((nb >> 1) & 1) == 0) {
            float n0 = bf_lo(k0) * bf_lo(k0) + bf_hi(k0) * bf_hi(k0);
            float n1 = bf_lo(k1) * bf_lo(k1) + bf_hi(k1) * bf_hi(k1);
            n0 += __shfl_xor_sync(0xffffffffu, n0, 1);
            n1 += __shfl_xor_sync(0xffffffffu, n1, 1);
            n0 += __shfl_xor_sync(0xffffffffu, n0, 2);
            n1 += __shfl_xor_sync(0xffffffffu, n1, 2);
            m = __uint_as_float(max(__float_as_uint(n0), __float_as_uint(n1)));
        } else {
            uint32_t u = max(max((k0 << 16) & 0x7FFFFFFFu, k0 & 0x7FFF0000u), max((k1 << 16) & 0x7FFFFFFFu, k1 & 0x7FFF0000u));
            m = __uint_as_float(u);
        }
        const unsigned int mu = __reduce_max_sync(0xffffffffu, __float_as_uint(m));
        if (lane == 0) atomicMax((unsigned int*)(smem + SM_MISC), mu);
        fence_async();
        asm volatile("bar.sync 1, 256;" ::: "memory");
        if (tid == 0) {
            g_nrm[blockIdx.x] = *(volatile float*)(smem + SM_MISC);
            signal(&g_ctr[br]);
        }
        const float qs = 0.25f * 1.4426950408889634f;
        unsigned char* qp = smem + SM_Q + wg * 2048 + lrow * 32 + c * 8;
#pragma unroll
        for (int h = 0; h < 8; h++) {
            const float* a = acc + h * 8;
            *(uint2*)(qp + h * 4096) = make_uint2(pack_bf16(a[0] * qs, a[1] * qs), pack_bf16(a[4] * qs, a[5] * qs));
            *(uint2*)(qp + h * 4096 + 256) = make_uint2(pack_bf16(a[2] * qs, a[3] * qs), pack_bf16(a[6] * qs, a[7] * qs));
        }
#pragma unroll
        for (int i = 0; i < 8; i++) *(uint4*)(smem + i * CHUNK_BYTES + 16384 + tid * 16) = make_uint4(0x00003F80u, 0, 0, 0);
        asm volatile("fence.proxy.async.shared::cta;" ::: "memory");
        ts_min(2); ts_max(18);
    } else if (wg == 2) {
        if (tid == 256) {
            for (int kb = 0; kb < 8; kb++) {
                const int st = kb % A_STAGES;
                if (kb >= A_STAGES) mbar_wait(sb + BAR_AE + st * 8, 0);
                const uint32_t s0 = sb + st * A_STAGE_BYTES, fb = sb + BAR_AF + st * 8;
                mbar_expect_tx(fb, A_STAGE_BYTES);
                tma_2d(s0, &maps.x, kb * 64, mb * 128, fb);
                tma_2d(s0 + 16384, &maps.wq[br], (nb & 3) * 128, kb * 64, fb);
                tma_2d(s0 + 24576, &maps.wq[br], (nb & 3) * 128 + 64, kb * 64, fb);
                tma_2d(s0 + 32768, &maps.wkv[nb >> 1], (nb & 1) * 8, kb * 64, fb);
            }
            l2_prefetch(woa + (size_t)blockIdx.x * 2048, 4096);
            l2_prefetch(wob + (size_t)blockIdx.x * 2048, 4096);
        }
        __syncwarp();
    } else {
        const int lane = tid & 31, w = (tid >> 5) & 3;
        const uint4* gw = (const uint4*)(gate_w + lane * 16);
        const uint4 w0 = __ldg(gw), w1 = __ldg(gw + 1);
        const uint32_t wv[8] = {w0.x, w0.y, w0.z, w0.w, w1.x, w1.y, w1.z, w1.w};
        uint4 xa[4][2];
#pragma unroll
        for (int rr = 0; rr < 4; rr++) {
            const uint4* xp = (const uint4*)(x + (size_t)(blockIdx.x * 16 + w * 4 + rr) * DM + lane * 16);
            xa[rr][0] = __ldg(xp);
            xa[rr][1] = __ldg(xp + 1);
        }
#pragma unroll
        for (int rr = 0; rr < 4; rr++) {
            const uint32_t xv[8] = {xa[rr][0].x, xa[rr][0].y, xa[rr][0].z, xa[rr][0].w, xa[rr][1].x, xa[rr][1].y, xa[rr][1].z, xa[rr][1].w};
            float sum = 0.f;
#pragma unroll
            for (int i = 0; i < 8; i++) {
                sum += bf_round(bf_lo(xv[i]) * bf_lo(wv[i]));
                sum += bf_round(bf_hi(xv[i]) * bf_hi(wv[i]));
            }
#pragma unroll
            for (int o = 16; o > 0; o >>= 1) sum += __shfl_xor_sync(0xffffffffu, sum, o);
            if (lane == 0) {
                sum = bf_round(sum);
                g_gate[blockIdx.x * 16 + w * 4 + rr] = bf_round(1.f / (1.f + __expf(-sum)));
            }
        }
    }
    __syncthreads();
    if (tid == 256) {
        spin_until(&g_ctr[br], 64);
        fence_async();
        ts_min(4); ts_max(20);
        const unsigned char* src = (const unsigned char*)g_KV + (size_t)br * 131072;
        for (int g = 0; g < 8; g++) {
            mbar_expect_tx(sb + BAR_KV + g * 8, 16384);
            bulk_g2s(sb + g * CHUNK_BYTES, src + g * 16384, 16384, sb + BAR_KV + g * 8);
        }
    }
    __syncwarp();

    {
        uint32_t c3f = 0x3F003F00u;
        asm volatile("" : "+r"(c3f));
        const uint64_t kd0 = make_desc(sb, 4096, 128, 0);
        const uint64_t vd0 = make_desc(sb + 8192, 128, 4096, 0);
#pragma unroll 1
        for (int t = 0; t < 4; t++) {
            uint32_t q[4];
            {
                const unsigned char* qp = smem + SM_Q + (wg * 4 + t) * 2048 + ((tid >> 5) & 3) * 512 + (tid & 31) * 8;
                const uint2 a = *(const uint2*)qp, b = *(const uint2*)(qp + 256);
                q[0] = a.x; q[2] = a.y; q[1] = b.x; q[3] = b.y;
            }
            float o[12];
            float s0[32], s1[32];
            uint32_t p[16];
#pragma unroll
            for (int i = 0; i < 12; i++) o[i] = 0.f;
            fence_regs<12>(o);
            {
                mbar_wait_u(sb + BAR_KV, 0);
                if (t == 0) { ts_min(5); ts_max(21); }
                wg_fence();
                qk_n64(s0, q, kd0);
                wg_commit();
                wg_wait<0>();
                fence_regs<32>(s0);
                uint64_t kd = kd0, vd = vd0;
#define HALF_STEP(SC, SN, KOFF, VOFF)                \
    wg_fence();                                      \
    qk_n64(SN, q, kd + (KOFF));                      \
    wg_commit();                                     \
    exp_half<0>(SC, p, c3f);                         \
    wg_fence();                                      \
    pv_n24(o, p, vd + (VOFF));                       \
    pv_n24(o, p + 4, vd + (VOFF) + 16);              \
    wg_commit();                                     \
    wg_wait<2>();                                    \
    exp_half<8>(SC + 16, p + 8, c3f);                \
    wg_fence();                                      \
    pv_n24(o, p + 8, vd + (VOFF) + 32);              \
    pv_n24(o, p + 12, vd + (VOFF) + 48);             \
    wg_commit();                                     \
    wg_wait<1>();                                    \
    fence_regs<32>(SN);
#pragma unroll 1
                for (uint32_t it = 0; it < 16; it++) {
                    mbar_wait_u(sb + BAR_KV + (((it >> 1) + 1) & 7) * 8, 0);
                    const uint64_t inc = (it & 1) ? 1152 : 128;
                    HALF_STEP(s0, s1, 64, 0)
                    HALF_STEP(s1, s0, inc, 64)
                    kd += inc;
                    vd += inc;
                }
                wg_wait<0>();
                fence_regs<12>(o);
            }
            {
                int tid2;
                asm volatile("mov.u32 %0, %%tid.x;" : "=r"(tid2));
                const int lane = tid2 & 31;
                const unsigned int na = __float_as_uint(__ldcg(g_nrm + (lane & 15) * 8 + br * 4 + (lane >> 4)));
                const unsigned int nv = __float_as_uint(__ldcg(g_nrm + (lane & 15) * 8 + br * 4 + 2 + (lane >> 4)));
                float n0 = bf_lo(q[0]) * bf_lo(q[0]) + bf_hi(q[0]) * bf_hi(q[0]) + bf_lo(q[2]) * bf_lo(q[2]) + bf_hi(q[2]) * bf_hi(q[2]);
                float n1 = bf_lo(q[1]) * bf_lo(q[1]) + bf_hi(q[1]) * bf_hi(q[1]) + bf_lo(q[3]) * bf_lo(q[3]) + bf_hi(q[3]) * bf_hi(q[3]);
                n0 += __shfl_xor_sync(0xffffffffu, n0, 1);
                n1 += __shfl_xor_sync(0xffffffffu, n1, 1);
                n0 += __shfl_xor_sync(0xffffffffu, n0, 2);
                n1 += __shfl_xor_sync(0xffffffffu, n1, 2);
                unsigned int h = na;
#pragma unroll
                for (int sft = 8; sft > 0; sft >>= 1) h = max(h, __shfl_xor_sync(0xffffffffu, h, sft));
                const float kmax2 = __uint_as_float(h) + __uint_as_float(__shfl_xor_sync(0xffffffffu, h, 16));
                const float vmax = __uint_as_float(__reduce_max_sync(0xffffffffu, nv));
                const bool unsafe = !(n0 * kmax2 <= 3600.f) || !(n1 * kmax2 <= 3600.f) || !(vmax <= 1.0e15f);
                uint32_t any_unsafe;
                asm volatile(
                    "{\n.reg .pred p, q;\nsetp.ne.u32 q, %1, 0;\nbar.red.or.pred p, %2, 128, q;\nselp.u32 %0, 1, 0, p;\n}"
                    : "=r"(any_unsafe) : "r"((uint32_t)unsafe), "r"(wg + 1) : "memory");
                if (__any_sync(0xffffffffu, any_unsafe)) {
#pragma unroll
                    for (int i = 0; i < 12; i++) o[i] = 0.f;
                    fence_regs<12>(o);
                    attn_tile_slow(q, kd0, vd0, o, s0, p);
                }
            }
            {
                int tid2;
                asm volatile("mov.u32 %0, %%tid.x;" : "=r"(tid2));
                const int lane = tid2 & 31;
                const float l0 = __shfl_sync(0xffffffffu, o[8], lane & ~3);
                const float l1 = __shfl_sync(0xffffffffu, o[10], lane & ~3);
                const float i0 = 1.f / l0, i1 = 1.f / l1;
                const int tile = wg * 4 + t;
                const uint32_t row = (uint32_t)(br * SEQ + mb * 128 + (tile & 1) * 64 + ((tid2 >> 5) & 3) * 16 + (lane >> 2));
                bf16* op = g_O + row * DM + ((nb & 3) * 8 + (tile >> 1)) * 16 + (lane & 3) * 2;
                *(uint32_t*)(op) = pack_bf16(o[0] * i0, o[1] * i0);
                *(uint32_t*)(op + 8 * DM) = pack_bf16(o[2] * i1, o[3] * i1);
                *(uint32_t*)(op + 8) = pack_bf16(o[4] * i0, o[5] * i0);
                *(uint32_t*)(op + 8 * DM + 8) = pack_bf16(o[6] * i1, o[7] * i1);
            }
        }
    }
    fence_async();
    asm volatile("bar.sync %0, 128;" ::"r"(wg + 1) : "memory");
    if ((tid & 127) == 0) signal(&g_ctr[2 + mb]);
    __syncthreads();
    ts_min(6); ts_max(22);

    const int orow0 = mb * 128 + (nb >> 2) * 64, ocol0 = (nb & 3) * 128;
    if (wg == 2) {
        if (tid == 288) {
            for (int i = 0; i < 2 * C_STAGES; i++) {
                const int kb = i >> 1, b = i & 1;
                const uint32_t s0 = sb + kb * C_STAGE_BYTES + b * 24576;
                mbar_expect_tx(sb + BAR_CF + i * 8, 24576);
                tma_2d(s0 + 8192, &maps.wo[b], ocol0, kb * 64, sb + BAR_CF + i * 8);
                tma_2d(s0 + 16384, &maps.wo[b], ocol0 + 64, kb * 64, sb + BAR_CF + i * 8);
            }
        }
        if (tid == 256) {
            spin_until(&g_ctr[2 + mb], 32);
            fence_async();
            for (int i = 0; i < 2 * C_STAGES; i++) {
                const int kb = i >> 1, b = i & 1;
                tma_2d(sb + kb * C_STAGE_BYTES + b * 24576, &maps.o, kb * 64, b * SEQ + orow0, sb + BAR_CF + i * 8);
            }
            for (int i = 0; i < 2 * C_STAGES; i++) {
                const int kb = C_STAGES + (i >> 1), b = i & 1;
                const uint32_t s0 = sb + (i >> 1) * C_STAGE_BYTES + b * 24576;
                mbar_wait(sb + BAR_CE + i * 8, 0);
                mbar_expect_tx(sb + BAR_CF + i * 8, 24576);
                tma_2d(s0, &maps.o, kb * 64, b * SEQ + orow0, sb + BAR_CF + i * 8);
                tma_2d(s0 + 8192, &maps.wo[b], ocol0, kb * 64, sb + BAR_CF + i * 8);
                tma_2d(s0 + 16384, &maps.wo[b], ocol0 + 64, kb * 64, sb + BAR_CF + i * 8);
            }
            __threadfence();
            if (atomicAdd(&g_ctr[18], 1u) == 127u) {
                for (int i = 0; i < 19; i++) g_ctr[i] = 0u;
            }
        }
    } else if (wg < 2) {
        const int warp = tid >> 5, lane = tid & 31;
        float acc[64];
#pragma unroll
        for (int i = 0; i < 64; i++) acc[i] = 0.f;
        fence_regs<64>(acc);
        const int r = lane >> 2, c = lane & 3;
        const int lrow = (warp & 3) * 16 + r;
        float g0 = 0.f, g1 = 0.f;
#pragma unroll
        for (int kb = 0; kb < 8; kb++) {
            const int st = kb % C_STAGES;
            const uint32_t s0 = sb + st * C_STAGE_BYTES + wg * 24576;
            mbar_wait_u(sb + BAR_CF + (st * 2 + wg) * 8, kb >= C_STAGES ? 1 : 0);
            if (kb == 0) {
                ts_min(8); ts_max(24);
                g0 = __ldcg(g_gate + orow0 + lrow);
                g1 = __ldcg(g_gate + orow0 + lrow + 8);
            }
            const uint64_t ad = make_desc(s0, 16, 1024, 1);
            const uint64_t bd = make_desc(s0 + 8192, 8192, 1024, 1);
            wg_fence();
#pragma unroll
            for (int kk = 0; kk < 4; kk++) mma_n128_ss(acc, ad + kk * 2, bd + kk * 128);
            wg_commit();
            if (kb >= 1 && kb <= C_STAGES) {
                wg_wait<1>();
                if (lane == 0) mbar_arrive(sb + BAR_CE + ((kb - 1) * 2 + wg) * 8);
            }
        }
        wg_wait<0>();
        fence_regs<64>(acc);
        ts_min(9); ts_max(25);
        if (wg) { g0 = bf_round(1.f - g0); g1 = bf_round(1.f - g1); }
        uint32_t t[32];
#pragma unroll
        for (int j = 0; j < 16; j++) {
            t[2 * j] = pack_bf16(g0 * bf_round(acc[4 * j]), g0 * bf_round(acc[4 * j + 1]));
            t[2 * j + 1] = pack_bf16(g1 * bf_round(acc[4 * j + 2]), g1 * bf_round(acc[4 * j + 3]));
        }
        uint32_t* xch = (uint32_t*)(smem + SM_XCH);
        const int lt = tid & 127;
#pragma unroll
        for (int j = 0; j < 16; j++) xch[(wg * 16 + j) * 128 + lt] = wg ? t[j] : t[16 + j];
        asm volatile("bar.sync 1, 256;" ::: "memory");
        unsigned char* ot = smem + wg * 16384;
#pragma unroll
        for (int j = 0; j < 16; j++) {
            const uint32_t mine = wg ? t[16 + j] : t[j];
            const uint32_t other = xch[((wg ^ 1) * 16 + j) * 128 + lt];
            const uint32_t v = pack_bf16(bf_lo(mine) + bf_lo(other), bf_hi(mine) + bf_hi(other));
            *(uint32_t*)(ot + (lrow + (j & 1) * 8) * 144 + (j >> 1) * 16 + c * 4) = v;
        }
        asm volatile("bar.sync %0, 128;" ::"r"(wg + 2) : "memory");
#pragma unroll
        for (int i = 0; i < 4; i++) {
            const int idx = i * 128 + lt, row = idx >> 3, ch = idx & 7;
            const uint4 v = *(const uint4*)(ot + row * 144 + ch * 16);
            *(uint4*)(out + (size_t)(orow0 + row) * DM + ocol0 + wg * 64 + ch * 8) = v;
        }
        ts_min(10); ts_max(26);
    }
}

typedef CUresult (*EncodeFn)(CUtensorMap*, CUtensorMapDataType, cuuint32_t, void*, const cuuint64_t*, const cuuint64_t*, const cuuint32_t*,
                             const cuuint32_t*, CUtensorMapInterleave, CUtensorMapSwizzle, CUtensorMapL2promotion, CUtensorMapFloatOOBfill);

static void encode_2d(EncodeFn fn, CUtensorMap* m, const void* ptr, uint64_t inner, uint64_t outer, uint32_t box_inner, uint32_t box_outer) {
    cuuint64_t dims[2] = {inner, outer};
    cuuint64_t strides[1] = {inner * 2};
    cuuint32_t box[2] = {box_inner, box_outer};
    cuuint32_t es[2] = {1, 1};
    fn(m, CU_TENSOR_MAP_DATA_TYPE_BFLOAT16, 2, (void*)ptr, dims, strides, box, es, CU_TENSOR_MAP_INTERLEAVE_NONE, CU_TENSOR_MAP_SWIZZLE_128B,
       CU_TENSOR_MAP_L2_PROMOTION_L2_256B, CU_TENSOR_MAP_FLOAT_OOB_FILL_NONE);
}

extern "C" void kernel_launch(void* const* d_in, const int* in_sizes, int n_in, void* d_out, int out_size) {
    (void)in_sizes; (void)n_in; (void)out_size;
    static Maps m;
    static const void* cached[11] = {0};
    static bool attr_done = false;
    bool same = true;
    for (int i = 0; i < 11; i++) same = same && (cached[i] == d_in[i]);
    if (!same || !attr_done) {
        void* fnp = nullptr;
        cudaDriverEntryPointQueryResult qr;
        cudaGetDriverEntryPoint("cuTensorMapEncodeTiled", &fnp, cudaEnableDefault, &qr);
        EncodeFn fn = (EncodeFn)fnp;
        void* po = nullptr;
        cudaGetSymbolAddress(&po, g_O);
        encode_2d(fn, &m.x, d_in[0], DM, SEQ, 64, 128);
        encode_2d(fn, &m.wq[0], d_in[1], DM, DM, 64, 64);
        encode_2d(fn, &m.wq[1], d_in[6], DM, DM, 64, 64);
        encode_2d(fn, &m.wkv[0], d_in[2], 16, DM, 64, 64);
        encode_2d(fn, &m.wkv[1], d_in[3], 16, DM, 64, 64);
        encode_2d(fn, &m.wkv[2], d_in[7], 16, DM, 64, 64);
        encode_2d(fn, &m.wkv[3], d_in[8], 16, DM, 64, 64);
        encode_2d(fn, &m.o, po, DM, 2 * SEQ, 64, 64);
        encode_2d(fn, &m.wo[0], d_in[4], DM, DM, 64, 64);
        encode_2d(fn, &m.wo[1], d_in[9], DM, DM, 64, 64);
        cudaFuncSetAttribute(fused_kernel, cudaFuncAttributeMaxDynamicSharedMemorySize, SMEM_TOTAL);
        for (int i = 0; i < 11; i++) cached[i] = d_in[i];
        attr_done = true;
    }
    cudaLaunchAttribute at[1];
    at[0].id = cudaLaunchAttributeCooperative;
    at[0].val.cooperative = 1;
    cudaLaunchConfig_t cfg = {};
    cfg.stream = cudaStreamPerThread;
    cfg.attrs = at;
    cfg.numAttrs = 1;
    cfg.gridDim = dim3(128);
    cfg.blockDim = dim3(512);
    cfg.dynamicSmemBytes = SMEM_TOTAL;
    cudaLaunchKernelEx(&cfg, fused_kernel, m, (const bf16*)d_in[0], (const bf16*)d_in[10], (const bf16*)d_in[1], (const bf16*)d_in[6],
                       (const bf16*)d_in[4], (const bf16*)d_in[9], (bf16*)d_out);
}
```

```cpp
#include <cuda_runtime.h>
#include <cuda_bf16.h>
#include <cuda.h>
#include <stdint.h>

typedef __nv_bfloat16 bf16;

#define SEQ 2048
#define DM 512
#define ROWS 65536

__device__ __align__(1024) bf16 g_KV[2 * 4 * SEQ * 8];
__device__ __align__(1024) bf16 g_O[2 * ROWS * 16];
__device__ float g_gate[SEQ];
__device__ __align__(16) float g_nrm[128];
__device__ unsigned int g_ctr[32];

#define ts_min(i)
#define ts_max(i)
__device__ __forceinline__ uint32_t smem_u32(const void* p) { return (uint32_t)__cvta_generic_to_shared(p); }
__device__ __forceinline__ uint64_t make_desc(uint32_t saddr, uint32_t lbo, uint32_t sbo, uint32_t swz) {
    uint64_t d = 0;
    d |= (uint64_t)((saddr & 0x3FFFF) >> 4);
    d |= (uint64_t)((lbo & 0x3FFFF) >> 4) << 16;
    d |= (uint64_t)((sbo & 0x3FFFF) >> 4) << 32;
    d |= (uint64_t)swz << 62;
    return d;
}
__device__ __forceinline__ void wg_fence() { asm volatile("wgmma.fence.sync.aligned;" ::: "memory"); }
__device__ __forceinline__ void wg_commit() { asm volatile("wgmma.commit_group.sync.aligned;" ::: "memory"); }
template <int N> __device__ __forceinline__ void wg_wait() { asm volatile("wgmma.wait_group.sync.aligned %0;" ::"n"(N) : "memory"); }
template <int N> __device__ __forceinline__ void fence_regs(float* d) {
#pragma unroll
    for (int i = 0; i < N; i++) asm volatile("" : "+f"(d[i])::"memory");
}
__device__ __forceinline__ void mbar_init(uint32_t bar, uint32_t cnt) { asm volatile("mbarrier.init.shared::cta.b64 [%0], %1;" ::"r"(bar), "r"(cnt)); }
__device__ __forceinline__ void mbar_expect_tx(uint32_t bar, uint32_t bytes) {
    asm volatile("mbarrier.arrive.expect_tx.shared::cta.b64 _, [%0], %1;" ::"r"(bar), "r"(bytes) : "memory");
}
__device__ __forceinline__ void mbar_arrive(uint32_t bar) { asm volatile("mbarrier.arrive.shared::cta.b64 _, [%0];" ::"r"(bar) : "memory"); }
__device__ __forceinline__ void mbar_wait(uint32_t bar, uint32_t parity) {
    asm volatile(
        "{\n.reg .pred p;\n"
        "WAIT_LOOP:\n"
        "mbarrier.try_wait.parity.shared::cta.b64 p, [%0], %1;\n"
        "@p bra DONE;\n"
        "bra WAIT_LOOP;\n"
        "DONE:\n}" ::"r"(bar), "r"(parity) : "memory");
}
__device__ __forceinline__ void mbar_wait_u(uint32_t bar, uint32_t parity) {
    uint32_t ok;
    do {
        asm volatile(
            "{\n.reg .pred p;\nmbarrier.try_wait.parity.shared::cta.b64 p, [%1], %2;\nselp.u32 %0, 1, 0, p;\n}"
            : "=r"(ok) : "r"(bar), "r"(parity) : "memory");
    } while (!__all_sync(0xffffffffu, ok));
}
__device__ __forceinline__ void bulk_g2s(uint32_t dst, const void* src, uint32_t bytes, uint32_t bar) {
    asm volatile("cp.async.bulk.shared::cluster.global.mbarrier::complete_tx::bytes [%0], [%1], %2, [%3];" ::"r"(dst), "l"(src), "r"(bytes), "r"(bar) : "memory");
}
__device__ __forceinline__ void tma_2d(uint32_t dst, const CUtensorMap* map, int c0, int c1, uint32_t bar) {
    asm volatile("cp.async.bulk.tensor.2d.shared::cluster.global.mbarrier::complete_tx::bytes [%0], [%1, {%3, %4}], [%2];" ::"r"(dst), "l"(map), "r"(bar), "r"(c0), "r"(c1) : "memory");
}
__device__ __forceinline__ void l2_prefetch(const void* p, uint32_t bytes) {
    asm volatile("cp.async.bulk.prefetch.L2.global [%0], %1;" ::"l"(p), "r"(bytes) : "memory");
}
__device__ __forceinline__ void pdl_launch() { asm volatile("griddepcontrol.launch_dependents;" ::: "memory"); }
__device__ __forceinline__ void pdl_wait() { asm volatile("griddepcontrol.wait;" ::: "memory"); }
__device__ __forceinline__ void fence_async() { asm volatile("fence.proxy.async;" ::: "memory"); }
__device__ __forceinline__ uint32_t pack_bf16(float lo, float hi) {
    uint32_t r;
    asm("cvt.rn.bf16x2.f32 %0, %1, %2;" : "=r"(r) : "f"(hi), "f"(lo));
    return r;
}
__device__ __forceinline__ float bf_lo(uint32_t u) { return __uint_as_float(u << 16); }
__device__ __forceinline__ float bf_hi(uint32_t u) { return __uint_as_float(u & 0xFFFF0000u); }
__device__ __forceinline__ float bf_round(float x) { return __bfloat162float(__float2bfloat16_rn(x)); }

#define A8(b) "+f"(d[b + 0]), "+f"(d[b + 1]), "+f"(d[b + 2]), "+f"(d[b + 3]), "+f"(d[b + 4]), "+f"(d[b + 5]), "+f"(d[b + 6]), "+f"(d[b + 7])
#define W8(b) "=f"(d[b + 0]), "=f"(d[b + 1]), "=f"(d[b + 2]), "=f"(d[b + 3]), "=f"(d[b + 4]), "=f"(d[b + 5]), "=f"(d[b + 6]), "=f"(d[b + 7])

__device__ __forceinline__ void mma_n136_ss(float* d, uint64_t ad, uint64_t bd) {
    asm volatile(
        "wgmma.mma_async.sync.aligned.m64n136k16.f32.bf16.bf16 "
        "{%0,%1,%2,%3,%4,%5,%6,%7,%8,%9,%10,%11,%12,%13,%14,%15,%16,%17,%18,%19,%20,%21,%22,%23,%24,%25,%26,%27,%28,%29,%30,%31,"
        "%32,%33,%34,%35,%36,%37,%38,%39,%40,%41,%42,%43,%44,%45,%46,%47,%48,%49,%50,%51,%52,%53,%54,%55,%56,%57,%58,%59,%60,%61,%62,%63,"
        "%64,%65,%66,%67}, %68, %69, 1, 1, 1, 0, 1;"
        : A8(0), A8(8), A8(16), A8(24), A8(32), A8(40), A8(48), A8(56), "+f"(d[64]), "+f"(d[65]), "+f"(d[66]), "+f"(d[67])
        : "l"(ad), "l"(bd));
}
__device__ __forceinline__ void mma_n128_ss(float* d, uint64_t ad, uint64_t bd) {
    asm volatile(
        "wgmma.mma_async.sync.aligned.m64n128k16.f32.bf16.bf16 "
        "{%0,%1,%2,%3,%4,%5,%6,%7,%8,%9,%10,%11,%12,%13,%14,%15,%16,%17,%18,%19,%20,%21,%22,%23,%24,%25,%26,%27,%28,%29,%30,%31,"
        "%32,%33,%34,%35,%36,%37,%38,%39,%40,%41,%42,%43,%44,%45,%46,%47,%48,%49,%50,%51,%52,%53,%54,%55,%56,%57,%58,%59,%60,%61,%62,%63}, "
        "%64, %65, 1, 1, 1, 0, 1;"
        : A8(0), A8(8), A8(16), A8(24), A8(32), A8(40), A8(48), A8(56)
        : "l"(ad), "l"(bd));
}
__device__ __forceinline__ void qk_n64(float* d, const uint32_t* a, uint64_t bd) {
    asm volatile(
        "wgmma.mma_async.sync.aligned.m64n64k16.f32.bf16.bf16 "
        "{%0,%1,%2,%3,%4,%5,%6,%7,%8,%9,%10,%11,%12,%13,%14,%15,%16,%17,%18,%19,%20,%21,%22,%23,%24,%25,%26,%27,%28,%29,%30,%31}, "
        "{%32,%33,%34,%35}, %36, 0, 1, 1, 0;"
        : W8(0), W8(8), W8(16), W8(24)
        : "r"(a[0]), "r"(a[1]), "r"(a[2]), "r"(a[3]), "l"(bd));
}
__device__ __forceinline__ void pv_n24(float* d, const uint32_t* a, uint64_t bd) {
    asm volatile(
        "wgmma.mma_async.sync.aligned.m64n24k16.f32.bf16.bf16 {%0,%1,%2,%3,%4,%5,%6,%7,%8,%9,%10,%11}, {%12,%13,%14,%15}, %16, 1, 1, 1, 1;"
        : A8(0), "+f"(d[8]), "+f"(d[9]), "+f"(d[10]), "+f"(d[11])
        : "r"(a[0]), "r"(a[1]), "r"(a[2]), "r"(a[3]), "l"(bd));
}

__device__ __forceinline__ float ex2(float x) {
    float e;
    asm("ex2.approx.ftz.f32 %0, %1;" : "=f"(e) : "f"(x));
    return e;
}
__device__ __forceinline__ uint32_t exp_pair_mufu(float x0, float x1) { return pack_bf16(ex2(x0), ex2(x1)); }

#define MAGIC0 (98304.0f + 127.0f - 75.0f / 128.0f)
#define MAGIC1 (98304.0f + 127.0f - 75.0f / 128.0f - 143.5f)
template <int PRM>
__device__ __forceinline__ uint32_t exp_pair_poly(float x0, float x1, uint32_t c3f) {
    float t0 = x0 + MAGIC0;
    float t1 = x1 + (PRM ? MAGIC0 : MAGIC1);
    uint32_t L, y2, E, r;
    if (PRM)
        asm("prmt.b32 %0, %1, %2, 0x5410;" : "=r"(L) : "r"(__float_as_uint(t0)), "r"(__float_as_uint(t1)));
    else
        L = __float_as_uint(t1) * 65536u + __float_as_uint(t0);
    asm("lop3.b32 %0, %1, 0x007F007F, %2, 0xEA;" : "=r"(y2) : "r"(L), "r"(c3f));
    E = L & 0x7F807F80u;
    asm("fma.rn.bf16x2 %0, %1, %2, %3;" : "=r"(r) : "r"(L), "r"(y2), "r"(E));
    return r;
}
#define EXP_MASK 0x4949u
template <int BASE>
__device__ __forceinline__ void exp_half(const float* s, uint32_t* p, uint32_t c3f) {
#pragma unroll
    for (int i = 0; i < 8; i++) {
        if ((EXP_MASK >> (BASE + i)) & 1) p[i] = exp_pair_mufu(s[2 * i], s[2 * i + 1]);
        else if (i & 1) p[i] = exp_pair_poly<1>(s[2 * i], s[2 * i + 1], c3f);
        else p[i] = exp_pair_poly<0>(s[2 * i], s[2 * i + 1], c3f);
    }
}

struct Maps {
    CUtensorMap x;
    CUtensorMap wq[2];
    CUtensorMap wkv[4];
    CUtensorMap o;
    CUtensorMap wo[2];
};
#define A_STAGES 4
#define A_STAGE_BYTES 40960
#define CHUNK_BYTES 20480
#define SM_Q 163840
#define C_STAGES 4
#define C_STAGE_BYTES 49152
#define SM_XCH 196608
#define SM_BAR 212992
#define BAR_AF (SM_BAR)
#define BAR_AE (SM_BAR + 32)
#define BAR_KV (SM_BAR + 64)
#define BAR_CF (SM_BAR + 128)
#define BAR_CE (SM_BAR + 192)
#define SM_MISC (SM_BAR + 256)
#define SMEM_TOTAL (SM_BAR + 1024 + 1024)

__device__ __forceinline__ void spin_until(const unsigned int* ctr, unsigned int target) {
    unsigned int v;
    for (unsigned int it = 0; it < (1u << 26); it++) {
        asm volatile("ld.acquire.gpu.global.u32 %0, [%1];" : "=r"(v) : "l"(ctr) : "memory");
        if (v >= target) return;
    }
    __trap();
}
__device__ __forceinline__ void signal(unsigned int* ctr) {
    asm volatile("red.release.gpu.global.add.u32 [%0], 1;" ::"l"(ctr) : "memory");
}

__device__ __forceinline__ void attn_tile_slow(const uint32_t* qq, uint64_t kd0, uint64_t vd0, float* o, float* s, uint32_t* p) {
    float m0 = -INFINITY, m1 = -INFINITY;
#pragma unroll 1
    for (int ch = 0; ch < 32; ch++) {
        wg_fence();
        qk_n64(s, qq, kd0 + (uint64_t)((ch >> 2) * 1280 + (ch & 3) * 64));
        wg_commit();
        wg_wait<0>();
        fence_regs<32>(s);
#pragma unroll
        for (int j = 0; j < 8; j++) {
            m0 = fmaxf(m0, fmaxf(s[4 * j], s[4 * j + 1]));
            m1 = fmaxf(m1, fmaxf(s[4 * j + 2], s[4 * j + 3]));
        }
    }
    m0 = fmaxf(m0, __shfl_xor_sync(0xffffffffu, m0, 1));
    m1 = fmaxf(m1, __shfl_xor_sync(0xffffffffu, m1, 1));
    m0 = fmaxf(m0, __shfl_xor_sync(0xffffffffu, m0, 2));
    m1 = fmaxf(m1, __shfl_xor_sync(0xffffffffu, m1, 2));
#pragma unroll 1
    for (int ch = 0; ch < 32; ch++) {
        wg_fence();
        qk_n64(s, qq, kd0 + (uint64_t)((ch >> 2) * 1280 + (ch & 3) * 64));
        wg_commit();
        wg_wait<0>();
        fence_regs<32>(s);
#pragma unroll
        for (int j = 0; j < 8; j++) {
            p[2 * j] = exp_pair_mufu(s[4 * j] - m0, s[4 * j + 1] - m0);
            p[2 * j + 1] = exp_pair_mufu(s[4 * j + 2] - m1, s[4 * j + 3] - m1);
        }
        wg_fence();
#pragma unroll
        for (int j = 0; j < 4; j++) pv_n24(o, p + 4 * j, vd0 + (uint64_t)((ch >> 2) * 1280 + (ch & 3) * 64 + 16 * j));
        wg_commit();
        wg_wait<0>();
        fence_regs<12>(o);
    }
}

__device__ __forceinline__ void store_o(const float* o, int br, int mb, int nb, int tile) {
    int tid2;
    asm volatile("mov.u32 %0, %%tid.x;" : "=r"(tid2));
    const int lane = tid2 & 31;
    const float l0 = __shfl_sync(0xffffffffu, o[8], lane & ~3);
    const float l1 = __shfl_sync(0xffffffffu, o[10], lane & ~3);
    const float i0 = 1.f / l0, i1 = 1.f / l1;
    const uint32_t row = (uint32_t)(br * SEQ + mb * 128 + (tile & 1) * 64 + ((tid2 >> 5) & 3) * 16 + (lane >> 2));
    bf16* op = g_O + row * DM + ((nb & 3) * 8 + (tile >> 1)) * 16 + (lane & 3) * 2;
    *(uint32_t*)(op) = pack_bf16(o[0] * i0, o[1] * i0);
    *(uint32_t*)(op + 8 * DM) = pack_bf16(o[2] * i1, o[3] * i1);
    *(uint32_t*)(op + 8) = pack_bf16(o[4] * i0, o[5] * i0);
    *(uint32_t*)(op + 8 * DM + 8) = pack_bf16(o[6] * i1, o[7] * i1);
}

__global__ void __launch_bounds__(512, 1) fused_kernel(const __grid_constant__ Maps maps, const bf16* __restrict__ x, const bf16* __restrict__ gate_w,
                                                        const bf16* __restrict__ wqa, const bf16* __restrict__ wqb, const bf16* __restrict__ woa,
                                                        const bf16* __restrict__ wob, bf16* __restrict__ out) {
    extern __shared__ unsigned char smem_raw[];
    const uint32_t sb = (smem_u32(smem_raw) + 1023) & ~1023u;
    unsigned char* smem = smem_raw + (sb - smem_u32(smem_raw));
    const int tid = threadIdx.x;
    const int wg = __shfl_sync(0xffffffffu, tid >> 7, 0);
    const int mb = blockIdx.x >> 3, nb = blockIdx.x & 7;
    const int br = nb >> 2;
    ts_min(0); ts_max(16);
    if (tid == 0) {
        for (int i = 0; i < 4; i++) {
            mbar_init(sb + BAR_AF + i * 8, 1);
            mbar_init(sb + BAR_AE + i * 8, 8);
        }
        for (int i = 0; i < 8; i++) {
            mbar_init(sb + BAR_KV + i * 8, 1);
            mbar_init(sb + BAR_CF + i * 8, 1);
            mbar_init(sb + BAR_CE + i * 8, 4);
        }
        *(unsigned int*)(smem + SM_MISC) = 0u;
        asm volatile("fence.mbarrier_init.release.cluster;" ::: "memory");
    }
    if (tid == 384) {
        l2_prefetch(x + (size_t)blockIdx.x * 8192, 16384);
        l2_prefetch(wqa + (size_t)blockIdx.x * 2048, 4096);
        l2_prefetch(wqb + (size_t)blockIdx.x * 2048, 4096);
    }
    __syncthreads();

    if (wg < 2) {
        const int warp = tid >> 5, lane = tid & 31;
        float acc[68];
#pragma unroll
        for (int i = 0; i < 68; i++) acc[i] = 0.f;
        fence_regs<68>(acc);
#pragma unroll
        for (int kb = 0; kb < 8; kb++) {
            const int st = kb % A_STAGES;
            const uint32_t s0 = sb + st * A_STAGE_BYTES;
            mbar_wait_u(sb + BAR_AF + st * 8, kb >= A_STAGES ? 1 : 0);
            if (kb == 0) { ts_min(12); ts_max(28); }
            const uint64_t ad = make_desc(s0 + wg * 8192, 16, 1024, 1);
            const uint64_t bd = make_desc(s0 + 16384, 8192, 1024, 1);
            wg_fence();
#pragma unroll
            for (int kk = 0; kk < 4; kk++) mma_n136_ss(acc, ad + kk * 2, bd + kk * 128);
            wg_commit();
            if (kb >= 1 && kb <= 8 - A_STAGES) {
                wg_wait<1>();
                if (lane == 0) mbar_arrive(sb + BAR_AE + (kb - 1) * 8);
            }
        }
        wg_wait<0>();
        fence_regs<68>(acc);
        ts_min(1); ts_max(17);
        const int r = lane >> 2, c = lane & 3;
        const int lrow = (warp & 3) * 16 + r;
        const int row = mb * 128 + wg * 64 + lrow;
        const uint32_t k0 = pack_bf16(acc[64], acc[65]), k1 = pack_bf16(acc[66], acc[67]);
        bf16* kvp = g_KV + (size_t)br * 65536 + (row >> 8) * 8192 + (nb & 3) * 2048 + (row & 255) * 8 + 2 * c;
        *(uint32_t*)kvp = k0;
        *(uint32_t*)(kvp + 64) = k1;
        float m;
        if (((nb >> 1) & 1) == 0) {
            float n0 = bf_lo(k0) * bf_lo(k0) + bf_hi(k0) * bf_hi(k0);
            float n1 = bf_lo(k1) * bf_lo(k1) + bf_hi(k1) * bf_hi(k1);
            n0 += __shfl_xor_sync(0xffffffffu, n0, 1);
            n1 += __shfl_xor_sync(0xffffffffu, n1, 1);
            n0 += __shfl_xor_sync(0xffffffffu, n0, 2);
            n1 += __shfl_xor_sync(0xffffffffu, n1, 2);
            m = __uint_as_float(max(__float_as_uint(n0), __float_as_uint(n1)));
        } else {
            uint32_t u = max(max((k0 << 16) & 0x7FFFFFFFu, k0 & 0x7FFF0000u), max((k1 << 16) & 0x7FFFFFFFu, k1 & 0x7FFF0000u));
            m = __uint_as_float(u);
        }
        const unsigned int mu = __reduce_max_sync(0xffffffffu, __float_as_uint(m));
        if (lane == 0) atomicMax((unsigned int*)(smem + SM_MISC), mu);
        fence_async();
        asm volatile("bar.sync 1, 256;" ::: "memory");
        if (tid == 0) {
            g_nrm[blockIdx.x] = *(volatile float*)(smem + SM_MISC);
            signal(&g_ctr[br]);
        }
        const float qs = 0.25f * 1.4426950408889634f;
        unsigned char* qp = smem + SM_Q + wg * 2048 + lrow * 32 + c * 8;
#pragma unroll
        for (int h = 0; h < 8; h++) {
            const float* a = acc + h * 8;
            *(uint2*)(qp + h * 4096) = make_uint2(pack_bf16(a[0] * qs, a[1] * qs), pack_bf16(a[4] * qs, a[5] * qs));
            *(uint2*)(qp + h * 4096 + 256) = make_uint2(pack_bf16(a[2] * qs, a[3] * qs), pack_bf16(a[6] * qs, a[7] * qs));
        }
#pragma unroll
        for (int i = 0; i < 8; i++) *(uint4*)(smem + i * CHUNK_BYTES + 16384 + tid * 16) = make_uint4(0x00003F80u, 0, 0, 0);
        asm volatile("fence.proxy.async.shared::cta;" ::: "memory");
        ts_min(2); ts_max(18);
    } else if (wg == 2) {
        if (tid == 256) {
            for (int kb = 0; kb < 8; kb++) {
                const int st = kb % A_STAGES;
                if (kb >= A_STAGES) mbar_wait(sb + BAR_AE + st * 8, 0);
                const uint32_t s0 = sb + st * A_STAGE_BYTES, fb = sb + BAR_AF + st * 8;
                mbar_expect_tx(fb, A_STAGE_BYTES);
                tma_2d(s0, &maps.x, kb * 64, mb * 128, fb);
                tma_2d(s0 + 16384, &maps.wq[br], (nb & 3) * 128, kb * 64, fb);
                tma_2d(s0 + 24576, &maps.wq[br], (nb & 3) * 128 + 64, kb * 64, fb);
                tma_2d(s0 + 32768, &maps.wkv[nb >> 1], (nb & 1) * 8, kb * 64, fb);
            }
            l2_prefetch(woa + (size_t)blockIdx.x * 2048, 4096);
            l2_prefetch(wob + (size_t)blockIdx.x * 2048, 4096);
        }
        __syncwarp();
    } else {
        const int lane = tid & 31, w = (tid >> 5) & 3;
        const uint4* gw = (const uint4*)(gate_w + lane * 16);
        const uint4 w0 = __ldg(gw), w1 = __ldg(gw + 1);
        const uint32_t wv[8] = {w0.x, w0.y, w0.z, w0.w, w1.x, w1.y, w1.z, w1.w};
        uint4 xa[4][2];
#pragma unroll
        for (int rr = 0; rr < 4; rr++) {
            const uint4* xp = (const uint4*)(x + (size_t)(blockIdx.x * 16 + w * 4 + rr) * DM + lane * 16);
            xa[rr][0] = __ldg(xp);
            xa[rr][1] = __ldg(xp + 1);
        }
#pragma unroll
        for (int rr = 0; rr < 4; rr++) {
            const uint32_t xv[8] = {xa[rr][0].x, xa[rr][0].y, xa[rr][0].z, xa[rr][0].w, xa[rr][1].x, xa[rr][1].y, xa[rr][1].z, xa[rr][1].w};
            float sum = 0.f;
#pragma unroll
            for (int i = 0; i < 8; i++) {
                sum += bf_round(bf_lo(xv[i]) * bf_lo(wv[i]));
                sum += bf_round(bf_hi(xv[i]) * bf_hi(wv[i]));
            }
#pragma unroll
            for (int o = 16; o > 0; o >>= 1) sum += __shfl_xor_sync(0xffffffffu, sum, o);
            if (lane == 0) {
                sum = bf_round(sum);
                g_gate[blockIdx.x * 16 + w * 4 + rr] = bf_round(1.f / (1.f + __expf(-sum)));
            }
        }
    }
    __syncthreads();
    if (tid == 256) {
        spin_until(&g_ctr[br], 64);
        fence_async();
        ts_min(4); ts_max(20);
        const unsigned char* src = (const unsigned char*)g_KV + (size_t)br * 131072;
        for (int g = 0; g < 8; g++) {
            mbar_expect_tx(sb + BAR_KV + g * 8, 16384);
            bulk_g2s(sb + g * CHUNK_BYTES, src + g * 16384, 16384, sb + BAR_KV + g * 8);
        }
    }
    __syncwarp();

    {
        uint32_t c3f = 0x3F003F00u;
        asm volatile("" : "+r"(c3f));
        const uint64_t kd0 = make_desc(sb, 4096, 128, 0);
        const uint64_t vd0 = make_desc(sb + 8192, 128, 4096, 0);
#pragma unroll 1
        for (int t = 0; t < 4; t++) {
            uint32_t q[4];
            {
                const unsigned char* qp = smem + SM_Q + (wg * 4 + t) * 2048 + ((tid >> 5) & 3) * 512 + (tid & 31) * 8;
                const uint2 a = *(const uint2*)qp, b = *(const uint2*)(qp + 256);
                q[0] = a.x; q[2] = a.y; q[1] = b.x; q[3] = b.y;
            }
            float o[12];
            float s0[32], s1[32];
            uint32_t p[16];
#pragma unroll
            for (int i = 0; i < 12; i++) o[i] = 0.f;
            fence_regs<12>(o);
            {
                mbar_wait_u(sb + BAR_KV, 0);
                if (t == 0) { ts_min(5); ts_max(21); }
                wg_fence();
                qk_n64(s0, q, kd0);
                wg_commit();
                wg_wait<0>();
                fence_regs<32>(s0);
                uint64_t kd = kd0, vd = vd0;
#define HALF_STEP(SC, SN, KOFF, VOFF)                \
    wg_fence();                                      \
    qk_n64(SN, q, kd + (KOFF));                      \
    wg_commit();                                     \
    exp_half<0>(SC, p, c3f);                         \
    wg_fence();                                      \
    pv_n24(o, p, vd + (VOFF));                       \
    pv_n24(o, p + 4, vd + (VOFF) + 16);              \
    wg_commit();                                     \
    wg_wait<2>();                                    \
    exp_half<8>(SC + 16, p + 8, c3f);                \
    wg_fence();                                      \
    pv_n24(o, p + 8, vd + (VOFF) + 32);              \
    pv_n24(o, p + 12, vd + (VOFF) + 48);             \
    wg_commit();                                     \
    wg_wait<1>();                                    \
    fence_regs<32>(SN);
#pragma unroll 1
                for (uint32_t it = 0; it < 16; it++) {
                    mbar_wait_u(sb + BAR_KV + (((it >> 1) + 1) & 7) * 8, 0);
                    const uint64_t inc = (it & 1) ? 1152 : 128;
                    HALF_STEP(s0, s1, 64, 0)
                    HALF_STEP(s1, s0, inc, 64)
                    kd += inc;
                    vd += inc;
                }
                wg_wait<0>();
                fence_regs<12>(o);
            }
            {
                int tid2;
                asm volatile("mov.u32 %0, %%tid.x;" : "=r"(tid2));
                const int lane = tid2 & 31;
                const unsigned int na = __float_as_uint(__ldcg(g_nrm + (lane & 15) * 8 + br * 4 + (lane >> 4)));
                const unsigned int nv = __float_as_uint(__ldcg(g_nrm + (lane & 15) * 8 + br * 4 + 2 + (lane >> 4)));
                float n0 = bf_lo(q[0]) * bf_lo(q[0]) + bf_hi(q[0]) * bf_hi(q[0]) + bf_lo(q[2]) * bf_lo(q[2]) + bf_hi(q[2]) * bf_hi(q[2]);
                float n1 = bf_lo(q[1]) * bf_lo(q[1]) + bf_hi(q[1]) * bf_hi(q[1]) + bf_lo(q[3]) * bf_lo(q[3]) + bf_hi(q[3]) * bf_hi(q[3]);
                n0 += __shfl_xor_sync(0xffffffffu, n0, 1);
                n1 += __shfl_xor_sync(0xffffffffu, n1, 1);
                n0 += __shfl_xor_sync(0xffffffffu, n0, 2);
                n1 += __shfl_xor_sync(0xffffffffu, n1, 2);
                unsigned int h = na;
#pragma unroll
                for (int sft = 8; sft > 0; sft >>= 1) h = max(h, __shfl_xor_sync(0xffffffffu, h, sft));
                const float kmax2 = __uint_as_float(h) + __uint_as_float(__shfl_xor_sync(0xffffffffu, h, 16));
                const float vmax = __uint_as_float(__reduce_max_sync(0xffffffffu, nv));
                const bool unsafe = !(n0 * kmax2 <= 3600.f) || !(n1 * kmax2 <= 3600.f) || !(vmax <= 1.0e15f);
                uint32_t any_unsafe;
                asm volatile(
                    "{\n.reg .pred p, q;\nsetp.ne.u32 q, %1, 0;\nbar.red.or.pred p, %2, 128, q;\nselp.u32 %0, 1, 0, p;\n}"
                    : "=r"(any_unsafe) : "r"((uint32_t)unsafe), "r"(wg + 1) : "memory");
                if (lane == 0) ((volatile uint32_t*)(smem + SM_MISC + 16))[(tid2 >> 5) * 4 + t] = any_unsafe;
            }
            store_o(o, br, mb, nb, wg * 4 + t);
        }
        __syncwarp();
#pragma unroll 1
        for (int t = 0; t < 4; t++) {
            if (!__any_sync(0xffffffffu, ((volatile uint32_t*)(smem + SM_MISC + 16))[(tid >> 5) * 4 + t])) continue;
            uint32_t q[4];
            {
                const unsigned char* qp = smem + SM_Q + (wg * 4 + t) * 2048 + ((tid >> 5) & 3) * 512 + (tid & 31) * 8;
                const uint2 a = *(const uint2*)qp, b = *(const uint2*)(qp + 256);
                q[0] = a.x; q[2] = a.y; q[1] = b.x; q[3] = b.y;
            }
            float o[12], s0[32];
            uint32_t p[16];
#pragma unroll
            for (int i = 0; i < 12; i++) o[i] = 0.f;
            fence_regs<12>(o);
            attn_tile_slow(q, kd0, vd0, o, s0, p);
            store_o(o, br, mb, nb, wg * 4 + t);
        }
    }
    fence_async();
    asm volatile("bar.sync %0, 128;" ::"r"(wg + 1) : "memory");
    if ((tid & 127) == 0) signal(&g_ctr[2 + mb]);
    __syncthreads();
    ts_min(6); ts_max(22);

    const int orow0 = mb * 128 + (nb >> 2) * 64, ocol0 = (nb & 3) * 128;
    if (wg == 2) {
        if (tid == 288) {
            for (int i = 0; i < 2 * C_STAGES; i++) {
                const int kb = i >> 1, b = i & 1;
                const uint32_t s0 = sb + kb * C_STAGE_BYTES + b * 24576;
                mbar_expect_tx(sb + BAR_CF + i * 8, 24576);
                tma_2d(s0 + 8192, &maps.wo[b], ocol0, kb * 64, sb + BAR_CF + i * 8);
                tma_2d(s0 + 16384, &maps.wo[b], ocol0 + 64, kb * 64, sb + BAR_CF + i * 8);
            }
        }
        if (tid == 256) {
            spin_until(&g_ctr[2 + mb], 32);
            fence_async();
            for (int i = 0; i < 2 * C_STAGES; i++) {
                const int kb = i >> 1, b = i & 1;
                tma_2d(sb + kb * C_STAGE_BYTES + b * 24576, &maps.o, kb * 64, b * SEQ + orow0, sb + BAR_CF + i * 8);
            }
            for (int i = 0; i < 2 * C_STAGES; i++) {
                const int kb = C_STAGES + (i >> 1), b = i & 1;
                const uint32_t s0 = sb + (i >> 1) * C_STAGE_BYTES + b * 24576;
                mbar_wait(sb + BAR_CE + i * 8, 0);
                mbar_expect_tx(sb + BAR_CF + i * 8, 24576);
                tma_2d(s0, &maps.o, kb * 64, b * SEQ + orow0, sb + BAR_CF + i * 8);
                tma_2d(s0 + 8192, &maps.wo[b], ocol0, kb * 64, sb + BAR_CF + i * 8);
                tma_2d(s0 + 16384, &maps.wo[b], ocol0 + 64, kb * 64, sb + BAR_CF + i * 8);
            }
            __threadfence();
            if (atomicAdd(&g_ctr[18], 1u) == 127u) {
                for (int i = 0; i < 19; i++) g_ctr[i] = 0u;
            }
        }
    } else if (wg < 2) {
        const int warp = tid >> 5, lane = tid & 31;
        float acc[64];
#pragma unroll
        for (int i = 0; i < 64; i++) acc[i] = 0.f;
        fence_regs<64>(acc);
        const int r = lane >> 2, c = lane & 3;
        const int lrow = (warp & 3) * 16 + r;
        float g0 = 0.f, g1 = 0.f;
#pragma unroll
        for (int kb = 0; kb < 8; kb++) {
            const int st = kb % C_STAGES;
            const uint32_t s0 = sb + st * C_STAGE_BYTES + wg * 24576;
            mbar_wait_u(sb + BAR_CF + (st * 2 + wg) * 8, kb >= C_STAGES ? 1 : 0);
            if (kb == 0) {
                ts_min(8); ts_max(24);
                g0 = __ldcg(g_gate + orow0 + lrow);
                g1 = __ldcg(g_gate + orow0 + lrow + 8);
            }
            const uint64_t ad = make_desc(s0, 16, 1024, 1);
            const uint64_t bd = make_desc(s0 + 8192, 8192, 1024, 1);
            wg_fence();
#pragma unroll
            for (int kk = 0; kk < 4; kk++) mma_n128_ss(acc, ad + kk * 2, bd + kk * 128);
            wg_commit();
            if (kb >= 1 && kb <= C_STAGES) {
                wg_wait<1>();
                if (lane == 0) mbar_arrive(sb + BAR_CE + ((kb - 1) * 2 + wg) * 8);
            }
        }
        wg_wait<0>();
        fence_regs<64>(acc);
        ts_min(9); ts_max(25);
        if (wg) { g0 = bf_round(1.f - g0); g1 = bf_round(1.f - g1); }
        uint32_t t[32];
#pragma unroll
        for (int j = 0; j < 16; j++) {
            t[2 * j] = pack_bf16(g0 * bf_round(acc[4 * j]), g0 * bf_round(acc[4 * j + 1]));
            t[2 * j + 1] = pack_bf16(g1 * bf_round(acc[4 * j + 2]), g1 * bf_round(acc[4 * j + 3]));
        }
        uint32_t* xch = (uint32_t*)(smem + SM_XCH);
        const int lt = tid & 127;
#pragma unroll
        for (int j = 0; j < 16; j++) xch[(wg * 16 + j) * 128 + lt] = wg ? t[j] : t[16 + j];
        asm volatile("bar.sync 1, 256;" ::: "memory");
        unsigned char* ot = smem + wg * 16384;
#pragma unroll
        for (int j = 0; j < 16; j++) {
            const uint32_t mine = wg ? t[16 + j] : t[j];
            const uint32_t other = xch[((wg ^ 1) * 16 + j) * 128 + lt];
            const uint32_t v = pack_bf16(bf_lo(mine) + bf_lo(other), bf_hi(mine) + bf_hi(other));
            *(uint32_t*)(ot + (lrow + (j & 1) * 8) * 144 + (j >> 1) * 16 + c * 4) = v;
        }
        asm volatile("bar.sync %0, 128;" ::"r"(wg + 2) : "memory");
#pragma unroll
        for (int i = 0; i < 4; i++) {
            const int idx = i * 128 + lt, row = idx >> 3, ch = idx & 7;
            const uint4 v = *(const uint4*)(ot + row * 144 + ch * 16);
            *(uint4*)(out + (size_t)(orow0 + row) * DM + ocol0 + wg * 64 + ch * 8) = v;
        }
        ts_min(10); ts_max(26);
    }
}

typedef CUresult (*EncodeFn)(CUtensorMap*, CUtensorMapDataType, cuuint32_t, void*, const cuuint64_t*, const cuuint64_t*, const cuuint32_t*,
                             const cuuint32_t*, CUtensorMapInterleave, CUtensorMapSwizzle, CUtensorMapL2promotion, CUtensorMapFloatOOBfill);

static void encode_2d(EncodeFn fn, CUtensorMap* m, const void* ptr, uint64_t inner, uint64_t outer, uint32_t box_inner, uint32_t box_outer) {
    cuuint64_t dims[2] = {inner, outer};
    cuuint64_t strides[1] = {inner * 2};
    cuuint32_t box[2] = {box_inner, box_outer};
    cuuint32_t es[2] = {1, 1};
    fn(m, CU_TENSOR_MAP_DATA_TYPE_BFLOAT16, 2, (void*)ptr, dims, strides, box, es, CU_TENSOR_MAP_INTERLEAVE_NONE, CU_TENSOR_MAP_SWIZZLE_128B,
       CU_TENSOR_MAP_L2_PROMOTION_L2_256B, CU_TENSOR_MAP_FLOAT_OOB_FILL_NONE);
}

extern "C" void kernel_launch(void* const* d_in, const int* in_sizes, int n_in, void* d_out, int out_size) {
    (void)in_sizes; (void)n_in; (void)out_size;
    static Maps m;
    static const void* cached[11] = {0};
    static bool attr_done = false;
    bool same = true;
    for (int i = 0; i < 11; i++) same = same && (cached[i] == d_in[i]);
    if (!same || !attr_done) {
        void* fnp = nullptr;
        cudaDriverEntryPointQueryResult qr;
        cudaGetDriverEntryPoint("cuTensorMapEncodeTiled", &fnp, cudaEnableDefault, &qr);
        EncodeFn fn = (EncodeFn)fnp;
        void* po = nullptr;
        cudaGetSymbolAddress(&po, g_O);
        encode_2d(fn, &m.x, d_in[0], DM, SEQ, 64, 128);
        encode_2d(fn, &m.wq[0], d_in[1], DM, DM, 64, 64);
        encode_2d(fn, &m.wq[1], d_in[6], DM, DM, 64, 64);
        encode_2d(fn, &m.wkv[0], d_in[2], 16, DM, 64, 64);
        encode_2d(fn, &m.wkv[1], d_in[3], 16, DM, 64, 64);
        encode_2d(fn, &m.wkv[2], d_in[7], 16, DM, 64, 64);
        encode_2d(fn, &m.wkv[3], d_in[8], 16, DM, 64, 64);
        encode_2d(fn, &m.o, po, DM, 2 * SEQ, 64, 64);
        encode_2d(fn, &m.wo[0], d_in[4], DM, DM, 64, 64);
        encode_2d(fn, &m.wo[1], d_in[9], DM, DM, 64, 64);
        cudaFuncSetAttribute(fused_kernel, cudaFuncAttributeMaxDynamicSharedMemorySize, SMEM_TOTAL);
        for (int i = 0; i < 11; i++) cached[i] = d_in[i];
        attr_done = true;
    }
    cudaLaunchAttribute at[1];
    at[0].id = cudaLaunchAttributeCooperative;
    at[0].val.cooperative = 1;
    cudaLaunchConfig_t cfg = {};
    cfg.stream = cudaStreamPerThread;
    cfg.attrs = at;
    cfg.numAttrs = 1;
    cfg.gridDim = dim3(128);
    cfg.blockDim = dim3(512);
    cfg.dynamicSmemBytes = SMEM_TOTAL;
    cudaLaunchKernelEx(&cfg, fused_kernel, m, (const bf16*)d_in[0], (const bf16*)d_in[10], (const bf16*)d_in[1], (const bf16*)d_in[6],
                       (const bf16*)d_in[4], (const bf16*)d_in[9], (bf16*)d_out);
}
```

```cpp
#include <cuda_runtime.h>
#include <cuda_bf16.h>
#include <cuda.h>
#include <stdint.h>

typedef __nv_bfloat16 bf16;

#define SEQ 2048
#define DM 512
#define ROWS 65536

__device__ __align__(1024) bf16 g_KV[2 * 4 * SEQ * 8];
__device__ __align__(1024) bf16 g_O[2 * ROWS * 16];
__device__ float g_gate[SEQ];
__device__ __align__(16) float g_nrm[128];
__device__ unsigned int g_ctr[32];

#define ts_min(i)
#define ts_max(i)
__device__ __forceinline__ uint32_t smem_u32(const void* p) { return (uint32_t)__cvta_generic_to_shared(p); }
__device__ __forceinline__ uint64_t make_desc(uint32_t saddr, uint32_t lbo, uint32_t sbo, uint32_t swz) {
    uint64_t d = 0;
    d |= (uint64_t)((saddr & 0x3FFFF) >> 4);
    d |= (uint64_t)((lbo & 0x3FFFF) >> 4) << 16;
    d |= (uint64_t)((sbo & 0x3FFFF) >> 4) << 32;
    d |= (uint64_t)swz << 62;
    return d;
}
__device__ __forceinline__ void wg_fence() { asm volatile("wgmma.fence.sync.aligned;" ::: "memory"); }
__device__ __forceinline__ void wg_commit() { asm volatile("wgmma.commit_group.sync.aligned;" ::: "memory"); }
template <int N> __device__ __forceinline__ void wg_wait() { asm volatile("wgmma.wait_group.sync.aligned %0;" ::"n"(N) : "memory"); }
template <int N> __device__ __forceinline__ void fence_regs(float* d) {
#pragma unroll
    for (int i = 0; i < N; i++) asm volatile("" : "+f"(d[i])::"memory");
}
__device__ __forceinline__ void mbar_init(uint32_t bar, uint32_t cnt) { asm volatile("mbarrier.init.shared::cta.b64 [%0], %1;" ::"r"(bar), "r"(cnt)); }
__device__ __forceinline__ void mbar_expect_tx(uint32_t bar, uint32_t bytes) {
    asm volatile("mbarrier.arrive.expect_tx.shared::cta.b64 _, [%0], %1;" ::"r"(bar), "r"(bytes) : "memory");
}
__device__ __forceinline__ void mbar_arrive(uint32_t bar) { asm volatile("mbarrier.arrive.shared::cta.b64 _, [%0];" ::"r"(bar) : "memory"); }
__device__ __forceinline__ void mbar_wait(uint32_t bar, uint32_t parity) {
    asm volatile(
        "{\n.reg .pred p;\n"
        "WAIT_LOOP:\n"
        "mbarrier.try_wait.parity.shared::cta.b64 p, [%0], %1;\n"
        "@p bra DONE;\n"
        "bra WAIT_LOOP;\n"
        "DONE:\n}" ::"r"(bar), "r"(parity) : "memory");
}
__device__ __forceinline__ void mbar_wait_u(uint32_t bar, uint32_t parity) {
    uint32_t ok;
    do {
        asm volatile(
            "{\n.reg .pred p;\nmbarrier.try_wait.parity.shared::cta.b64 p, [%1], %2;\nselp.u32 %0, 1, 0, p;\n}"
            : "=r"(ok) : "r"(bar), "r"(parity) : "memory");
    } while (!__all_sync(0xffffffffu, ok));
}
__device__ __forceinline__ void bulk_g2s(uint32_t dst, const void* src, uint32_t bytes, uint32_t bar) {
    asm volatile("cp.async.bulk.shared::cluster.global.mbarrier::complete_tx::bytes [%0], [%1], %2, [%3];" ::"r"(dst), "l"(src), "r"(bytes), "r"(bar) : "memory");
}
__device__ __forceinline__ void tma_2d(uint32_t dst, const CUtensorMap* map, int c0, int c1, uint32_t bar) {
    asm volatile("cp.async.bulk.tensor.2d.shared::cluster.global.mbarrier::complete_tx::bytes [%0], [%1, {%3, %4}], [%2];" ::"r"(dst), "l"(map), "r"(bar), "r"(c0), "r"(c1) : "memory");
}
__device__ __forceinline__ void l2_prefetch(const void* p, uint32_t bytes) {
    asm volatile("cp.async.bulk.prefetch.L2.global [%0], %1;" ::"l"(p), "r"(bytes) : "memory");
}
__device__ __forceinline__ void pdl_launch() { asm volatile("griddepcontrol.launch_dependents;" ::: "memory"); }
__device__ __forceinline__ void pdl_wait() { asm volatile("griddepcontrol.wait;" ::: "memory"); }
__device__ __forceinline__ void fence_async() { asm volatile("fence.proxy.async;" ::: "memory"); }
__device__ __forceinline__ uint32_t pack_bf16(float lo, float hi) {
    uint32_t r;
    asm("cvt.rn.bf16x2.f32 %0, %1, %2;" : "=r"(r) : "f"(hi), "f"(lo));
    return r;
}
__device__ __forceinline__ float bf_lo(uint32_t u) { return __uint_as_float(u << 16); }
__device__ __forceinline__ float bf_hi(uint32_t u) { return __uint_as_float(u & 0xFFFF0000u); }
__device__ __forceinline__ float bf_round(float x) { return __bfloat162float(__float2bfloat16_rn(x)); }

#define A8(b) "+f"(d[b + 0]), "+f"(d[b + 1]), "+f"(d[b + 2]), "+f"(d[b + 3]), "+f"(d[b + 4]), "+f"(d[b + 5]), "+f"(d[b + 6]), "+f"(d[b + 7])
#define W8(b) "=f"(d[b + 0]), "=f"(d[b + 1]), "=f"(d[b + 2]), "=f"(d[b + 3]), "=f"(d[b + 4]), "=f"(d[b + 5]), "=f"(d[b + 6]), "=f"(d[b + 7])

__device__ __forceinline__ void mma_n8_ss(float* d, uint64_t ad, uint64_t bd) {
    asm volatile("wgmma.mma_async.sync.aligned.m64n8k16.f32.bf16.bf16 {%0,%1,%2,%3}, %4, %5, 1, 1, 1, 0, 1;"
                 : "+f"(d[0]), "+f"(d[1]), "+f"(d[2]), "+f"(d[3])
                 : "l"(ad), "l"(bd));
}
__device__ __forceinline__ void mma_n128_ss(float* d, uint64_t ad, uint64_t bd) {
    asm volatile(
        "wgmma.mma_async.sync.aligned.m64n128k16.f32.bf16.bf16 "
        "{%0,%1,%2,%3,%4,%5,%6,%7,%8,%9,%10,%11,%12,%13,%14,%15,%16,%17,%18,%19,%20,%21,%22,%23,%24,%25,%26,%27,%28,%29,%30,%31,"
        "%32,%33,%34,%35,%36,%37,%38,%39,%40,%41,%42,%43,%44,%45,%46,%47,%48,%49,%50,%51,%52,%53,%54,%55,%56,%57,%58,%59,%60,%61,%62,%63}, "
        "%64, %65, 1, 1, 1, 0, 1;"
        : A8(0), A8(8), A8(16), A8(24), A8(32), A8(40), A8(48), A8(56)
        : "l"(ad), "l"(bd));
}
__device__ __forceinline__ void qk_n64(float* d, const uint32_t* a, uint64_t bd) {
    asm volatile(
        "wgmma.mma_async.sync.aligned.m64n64k16.f32.bf16.bf16 "
        "{%0,%1,%2,%3,%4,%5,%6,%7,%8,%9,%10,%11,%12,%13,%14,%15,%16,%17,%18,%19,%20,%21,%22,%23,%24,%25,%26,%27,%28,%29,%30,%31}, "
        "{%32,%33,%34,%35}, %36, 0, 1, 1, 0;"
        : W8(0), W8(8), W8(16), W8(24)
        : "r"(a[0]), "r"(a[1]), "r"(a[2]), "r"(a[3]), "l"(bd));
}
__device__ __forceinline__ void pv_n24(float* d, const uint32_t* a, uint64_t bd) {
    asm volatile(
        "wgmma.mma_async.sync.aligned.m64n24k16.f32.bf16.bf16 {%0,%1,%2,%3,%4,%5,%6,%7,%8,%9,%10,%11}, {%12,%13,%14,%15}, %16, 1, 1, 1, 1;"
        : A8(0), "+f"(d[8]), "+f"(d[9]), "+f"(d[10]), "+f"(d[11])
        : "r"(a[0]), "r"(a[1]), "r"(a[2]), "r"(a[3]), "l"(bd));
}

__device__ __forceinline__ float ex2(float x) {
    float e;
    asm("ex2.approx.ftz.f32 %0, %1;" : "=f"(e) : "f"(x));
    return e;
}
__device__ __forceinline__ uint32_t exp_pair_mufu(float x0, float x1) { return pack_bf16(ex2(x0), ex2(x1)); }

#define MAGIC0 (98304.0f + 127.0f - 75.0f / 128.0f)
#define MAGIC1 (98304.0f + 127.0f - 75.0f / 128.0f - 143.5f)
template <int PRM>
__device__ __forceinline__ uint32_t exp_pair_poly(float x0, float x1, uint32_t c3f) {
    float t0 = x0 + MAGIC0;
    float t1 = x1 + (PRM ? MAGIC0 : MAGIC1);
    uint32_t L, y2, E, r;
    if (PRM)
        asm("prmt.b32 %0, %1, %2, 0x5410;" : "=r"(L) : "r"(__float_as_uint(t0)), "r"(__float_as_uint(t1)));
    else
        L = __float_as_uint(t1) * 65536u + __float_as_uint(t0);
    asm("lop3.b32 %0, %1, 0x007F007F, %2, 0xEA;" : "=r"(y2) : "r"(L), "r"(c3f));
    E = L & 0x7F807F80u;
    asm("fma.rn.bf16x2 %0, %1, %2, %3;" : "=r"(r) : "r"(L), "r"(y2), "r"(E));
    return r;
}
#define EXP_MASK 0x4949u
template <int BASE>
__device__ __forceinline__ void exp_half(const float* s, uint32_t* p, uint32_t c3f) {
#pragma unroll
    for (int i = 0; i < 8; i++) {
        if ((EXP_MASK >> (BASE + i)) & 1) p[i] = exp_pair_mufu(s[2 * i], s[2 * i + 1]);
        else if (i & 1) p[i] = exp_pair_poly<1>(s[2 * i], s[2 * i + 1], c3f);
        else p[i] = exp_pair_poly<0>(s[2 * i], s[2 * i + 1], c3f);
    }
}

struct Maps {
    CUtensorMap x;
    CUtensorMap wq[2];
    CUtensorMap wkv[4];
    CUtensorMap o;
    CUtensorMap wo[2];
};
#define SM_X 20480
#define SM_WKV 151552
#define SM_WQ 159744
#define CHUNK_BYTES 20480
#define SM_Q 163840
#define C_STAGES 4
#define C_STAGE_BYTES 49152
#define SM_XCH 196608
#define SM_BAR 225280
#define BAR_X (SM_BAR)
#define BAR_KV (SM_BAR + 64)
#define BAR_CF (SM_BAR + 128)
#define BAR_CE (SM_BAR + 192)
#define BAR_WF (SM_BAR + 256)
#define BAR_WE (SM_BAR + 288)
#define BAR_WKV (SM_BAR + 320)
#define SM_MISC (SM_BAR + 384)
#define SMEM_TOTAL (SM_BAR + 1024 + 1024)

__device__ __forceinline__ void spin_until(const unsigned int* ctr, unsigned int target) {
    unsigned int v;
    for (unsigned int it = 0; it < (1u << 26); it++) {
        asm volatile("ld.acquire.gpu.global.u32 %0, [%1];" : "=r"(v) : "l"(ctr) : "memory");
        if (v >= target) return;
    }
    __trap();
}
__device__ __forceinline__ void signal(unsigned int* ctr) {
    asm volatile("red.release.gpu.global.add.u32 [%0], 1;" ::"l"(ctr) : "memory");
}

__device__ __forceinline__ void attn_tile_slow(const uint32_t* qq, uint64_t kd0, uint64_t vd0, float* o, float* s, uint32_t* p) {
    float m0 = -INFINITY, m1 = -INFINITY;
#pragma unroll 1
    for (int ch = 0; ch < 32; ch++) {
        wg_fence();
        qk_n64(s, qq, kd0 + (uint64_t)((ch >> 2) * 1280 + (ch & 3) * 64));
        wg_commit();
        wg_wait<0>();
        fence_regs<32>(s);
#pragma unroll
        for (int j = 0; j < 8; j++) {
            m0 = fmaxf(m0, fmaxf(s[4 * j], s[4 * j + 1]));
            m1 = fmaxf(m1, fmaxf(s[4 * j + 2], s[4 * j + 3]));
        }
    }
    m0 = fmaxf(m0, __shfl_xor_sync(0xffffffffu, m0, 1));
    m1 = fmaxf(m1, __shfl_xor_sync(0xffffffffu, m1, 1));
    m0 = fmaxf(m0, __shfl_xor_sync(0xffffffffu, m0, 2));
    m1 = fmaxf(m1, __shfl_xor_sync(0xffffffffu, m1, 2));
#pragma unroll 1
    for (int ch = 0; ch < 32; ch++) {
        wg_fence();
        qk_n64(s, qq, kd0 + (uint64_t)((ch >> 2) * 1280 + (ch & 3) * 64));
        wg_commit();
        wg_wait<0>();
        fence_regs<32>(s);
#pragma unroll
        for (int j = 0; j < 8; j++) {
            p[2 * j] = exp_pair_mufu(s[4 * j] - m0, s[4 * j + 1] - m0);
            p[2 * j + 1] = exp_pair_mufu(s[4 * j + 2] - m1, s[4 * j + 3] - m1);
        }
        wg_fence();
#pragma unroll
        for (int j = 0; j < 4; j++) pv_n24(o, p + 4 * j, vd0 + (uint64_t)((ch >> 2) * 1280 + (ch & 3) * 64 + 16 * j));
        wg_commit();
        wg_wait<0>();
        fence_regs<12>(o);
    }
}

__device__ __forceinline__ void store_o(const float* o, int br, int mb, int nb, int tile) {
    int tid2;
    asm volatile("mov.u32 %0, %%tid.x;" : "=r"(tid2));
    const int lane = tid2 & 31;
    const float l0 = __shfl_sync(0xffffffffu, o[8], lane & ~3);
    const float l1 = __shfl_sync(0xffffffffu, o[10], lane & ~3);
    const float i0 = 1.f / l0, i1 = 1.f / l1;
    const uint32_t row = (uint32_t)(br * SEQ + mb * 128 + (tile & 1) * 64 + ((tid2 >> 5) & 3) * 16 + (lane >> 2));
    bf16* op = g_O + row * DM + ((nb & 3) * 8 + (tile >> 1)) * 16 + (lane & 3) * 2;
    *(uint32_t*)(op) = pack_bf16(o[0] * i0, o[1] * i0);
    *(uint32_t*)(op + 8 * DM) = pack_bf16(o[2] * i1, o[3] * i1);
    *(uint32_t*)(op + 8) = pack_bf16(o[4] * i0, o[5] * i0);
    *(uint32_t*)(op + 8 * DM + 8) = pack_bf16(o[6] * i1, o[7] * i1);
}

__global__ void __launch_bounds__(512, 1) fused_kernel(const __grid_constant__ Maps maps, const bf16* __restrict__ x, const bf16* __restrict__ gate_w,
                                                        const bf16* __restrict__ wqa, const bf16* __restrict__ wqb, const bf16* __restrict__ woa,
                                                        const bf16* __restrict__ wob, bf16* __restrict__ out) {
    extern __shared__ unsigned char smem_raw[];
    const uint32_t sb = (smem_u32(smem_raw) + 1023) & ~1023u;
    unsigned char* smem = smem_raw + (sb - smem_u32(smem_raw));
    const int tid = threadIdx.x;
    const int wg = __shfl_sync(0xffffffffu, tid >> 7, 0);
    const int mb = blockIdx.x >> 3, nb = blockIdx.x & 7;
    const int br = nb >> 2;
    ts_min(0); ts_max(16);
    if (tid == 0) {
        for (int i = 0; i < 8; i++) {
            mbar_init(sb + BAR_X + i * 8, 1);
            mbar_init(sb + BAR_KV + i * 8, 1);
            mbar_init(sb + BAR_CF + i * 8, 1);
            mbar_init(sb + BAR_CE + i * 8, 4);
        }
        for (int i = 0; i < 4; i++) {
            mbar_init(sb + BAR_WF + i * 8, 1);
            mbar_init(sb + BAR_WE + i * 8, 8);
        }
        mbar_init(sb + BAR_WKV, 1);
        *(unsigned int*)(smem + SM_MISC) = 0u;
        asm volatile("fence.mbarrier_init.release.cluster;" ::: "memory");
    }
    if (tid == 416) {
        l2_prefetch(x + (size_t)blockIdx.x * 8192, 16384);
        l2_prefetch(wqa + (size_t)blockIdx.x * 2048, 4096);
        l2_prefetch(wqb + (size_t)blockIdx.x * 2048, 4096);
    }
    __syncthreads();

    const unsigned char* kv_src = (const unsigned char*)g_KV + (size_t)br * 131072;
    if (wg < 2) {
        const int warp = tid >> 5, lane = tid & 31;
        float acc[64];
#pragma unroll
        for (int i = 0; i < 64; i++) acc[i] = 0.f;
        fence_regs<64>(acc);
#pragma unroll
        for (int kb = 0; kb < 8; kb++) {
            const int st = kb & 3;
            mbar_wait_u(sb + BAR_X + kb * 8, 0);
            mbar_wait_u(sb + BAR_WF + st * 8, kb >> 2);
            if (kb == 0) { ts_min(12); ts_max(28); }
            const uint64_t ad = make_desc(sb + SM_X + kb * 16384 + wg * 8192, 16, 1024, 1);
            const uint64_t bd = make_desc(sb + SM_WQ + st * 16384, 8192, 1024, 1);
            wg_fence();
#pragma unroll
            for (int kk = 0; kk < 4; kk++) mma_n128_ss(acc, ad + kk * 2, bd + kk * 128);
            wg_commit();
            if (kb >= 1 && kb <= 4) {
                wg_wait<1>();
                if (lane == 0) mbar_arrive(sb + BAR_WE + (kb - 1) * 8);
            }
        }
        wg_wait<0>();
        fence_regs<64>(acc);
        ts_min(1); ts_max(17);
        asm volatile("bar.sync 1, 384;" ::: "memory");
        const int r = lane >> 2, c = lane & 3;
        const float qs = 0.25f * 1.4426950408889634f;
        unsigned char* qp = smem + SM_Q + wg * 2048 + ((warp & 3) * 16 + r) * 32 + c * 8;
#pragma unroll
        for (int h = 0; h < 8; h++) {
            const float* a = acc + h * 8;
            *(uint2*)(qp + h * 4096) = make_uint2(pack_bf16(a[0] * qs, a[1] * qs), pack_bf16(a[4] * qs, a[5] * qs));
            *(uint2*)(qp + h * 4096 + 256) = make_uint2(pack_bf16(a[2] * qs, a[3] * qs), pack_bf16(a[6] * qs, a[7] * qs));
        }
        ts_min(2); ts_max(18);
    } else if (wg == 2) {
        const int warp = (tid >> 5) & 3, lane = tid & 31;
        float a0[4] = {0.f, 0.f, 0.f, 0.f}, a1[4] = {0.f, 0.f, 0.f, 0.f};
        fence_regs<4>(a0);
        fence_regs<4>(a1);
        *(uint4*)(smem + 16384 + (tid & 127) * 16) = make_uint4(0x00003F80u, 0, 0, 0);
        *(uint4*)(smem + 18432 + (tid & 127) * 16) = make_uint4(0x00003F80u, 0, 0, 0);
        mbar_wait_u(sb + BAR_WKV, 0);
#pragma unroll
        for (int kb = 0; kb < 8; kb++) {
            mbar_wait_u(sb + BAR_X + kb * 8, 0);
            const uint64_t ad = make_desc(sb + SM_X + kb * 16384, 16, 1024, 1);
            const uint64_t bd = make_desc(sb + SM_WKV + kb * 1024, 128, 128, 0);
            wg_fence();
#pragma unroll
            for (int kk = 0; kk < 4; kk++) {
                mma_n8_ss(a0, ad + kk * 2, bd + kk * 16);
                mma_n8_ss(a1, ad + 512 + kk * 2, bd + kk * 16);
            }
            wg_commit();
        }
        wg_wait<0>();
        fence_regs<4>(a0);
        fence_regs<4>(a1);
        const int r = lane >> 2, c = lane & 3;
        const int row = mb * 128 + warp * 16 + r;
        const uint32_t k0 = pack_bf16(a0[0], a0[1]), k1 = pack_bf16(a0[2], a0[3]);
        const uint32_t k2 = pack_bf16(a1[0], a1[1]), k3 = pack_bf16(a1[2], a1[3]);
        bf16* kvp = g_KV + (size_t)br * 65536 + (row >> 8) * 8192 + (nb & 3) * 2048 + (row & 255) * 8 + 2 * c;
        *(uint32_t*)kvp = k0;
        *(uint32_t*)(kvp + 64) = k1;
        *(uint32_t*)(kvp + 512) = k2;
        *(uint32_t*)(kvp + 576) = k3;
        unsigned int mu;
        if (((nb >> 1) & 1) == 0) {
            float n0 = bf_lo(k0) * bf_lo(k0) + bf_hi(k0) * bf_hi(k0);
            float n1 = bf_lo(k1) * bf_lo(k1) + bf_hi(k1) * bf_hi(k1);
            float n2 = bf_lo(k2) * bf_lo(k2) + bf_hi(k2) * bf_hi(k2);
            float n3 = bf_lo(k3) * bf_lo(k3) + bf_hi(k3) * bf_hi(k3);
#pragma unroll
            for (int sft = 1; sft <= 2; sft <<= 1) {
                n0 += __shfl_xor_sync(0xffffffffu, n0, sft);
                n1 += __shfl_xor_sync(0xffffffffu, n1, sft);
                n2 += __shfl_xor_sync(0xffffffffu, n2, sft);
                n3 += __shfl_xor_sync(0xffffffffu, n3, sft);
            }
            mu = max(max(__float_as_uint(n0), __float_as_uint(n1)), max(__float_as_uint(n2), __float_as_uint(n3)));
        } else {
            mu = max(max(max((k0 << 16) & 0x7FFFFFFFu, k0 & 0x7FFF0000u), max((k1 << 16) & 0x7FFFFFFFu, k1 & 0x7FFF0000u)),
                     max(max((k2 << 16) & 0x7FFFFFFFu, k2 & 0x7FFF0000u), max((k3 << 16) & 0x7FFFFFFFu, k3 & 0x7FFF0000u)));
        }
        mu = __reduce_max_sync(0xffffffffu, mu);
        if (lane == 0) atomicMax((unsigned int*)(smem + SM_MISC), mu);
        fence_async();
        asm volatile("bar.sync 2, 128;" ::: "memory");
        if (tid == 256) {
            g_nrm[blockIdx.x] = *(volatile float*)(smem + SM_MISC);
            signal(&g_ctr[br]);
            ts_min(13); ts_max(29);
        }
        asm volatile("bar.sync 1, 384;" ::: "memory");
#pragma unroll
        for (int i = 1; i < 8; i++) {
            *(uint4*)(smem + i * CHUNK_BYTES + 16384 + (tid & 127) * 16) = make_uint4(0x00003F80u, 0, 0, 0);
            *(uint4*)(smem + i * CHUNK_BYTES + 18432 + (tid & 127) * 16) = make_uint4(0x00003F80u, 0, 0, 0);
        }
        asm volatile("fence.proxy.async.shared::cta;" ::: "memory");
    } else {
        const int lane = tid & 31, w = (tid >> 5) & 3;
        if (w == 0) {
            if (lane == 0) {
                for (int kb = 0; kb < 8; kb++) {
                    mbar_expect_tx(sb + BAR_X + kb * 8, 16384);
                    tma_2d(sb + SM_X + kb * 16384, &maps.x, kb * 64, mb * 128, sb + BAR_X + kb * 8);
                    if (kb == 0) {
                        mbar_expect_tx(sb + BAR_WKV, 8192);
                        tma_2d(sb + SM_WKV, &maps.wkv[nb >> 1], (nb & 1) * 8, 0, sb + BAR_WKV);
                        tma_2d(sb + SM_WKV + 4096, &maps.wkv[nb >> 1], (nb & 1) * 8, 256, sb + BAR_WKV);
                    }
                    if (kb & 1) {
                        const int st = kb >> 1;
                        mbar_expect_tx(sb + BAR_WF + st * 8, 16384);
                        tma_2d(sb + SM_WQ + st * 16384, &maps.wq[br], (nb & 3) * 128, st * 64, sb + BAR_WF + st * 8);
                        tma_2d(sb + SM_WQ + st * 16384 + 8192, &maps.wq[br], (nb & 3) * 128 + 64, st * 64, sb + BAR_WF + st * 8);
                    }
                }
                for (int st = 0; st < 4; st++) {
                    mbar_wait(sb + BAR_WE + st * 8, 0);
                    mbar_expect_tx(sb + BAR_WF + st * 8, 16384);
                    tma_2d(sb + SM_WQ + st * 16384, &maps.wq[br], (nb & 3) * 128, (st + 4) * 64, sb + BAR_WF + st * 8);
                    tma_2d(sb + SM_WQ + st * 16384 + 8192, &maps.wq[br], (nb & 3) * 128 + 64, (st + 4) * 64, sb + BAR_WF + st * 8);
                }
                l2_prefetch(woa + (size_t)blockIdx.x * 2048, 4096);
                l2_prefetch(wob + (size_t)blockIdx.x * 2048, 4096);
                spin_until(&g_ctr[br], 64);
                fence_async();
                ts_min(4); ts_max(20);
                mbar_expect_tx(sb + BAR_KV, 16384);
                bulk_g2s(sb, kv_src, 16384, sb + BAR_KV);
            }
            __syncwarp();
            unsigned int h = __float_as_uint(__ldcg(g_nrm + (lane & 15) * 8 + br * 4 + (lane >> 4)));
            const unsigned int nv = __float_as_uint(__ldcg(g_nrm + (lane & 15) * 8 + br * 4 + 2 + (lane >> 4)));
#pragma unroll
            for (int sft = 8; sft > 0; sft >>= 1) h = max(h, __shfl_xor_sync(0xffffffffu, h, sft));
            float kmax2 = __uint_as_float(h) + __uint_as_float(__shfl_xor_sync(0xffffffffu, h, 16));
            const float vmax = __uint_as_float(__reduce_max_sync(0xffffffffu, nv));
            if (!(vmax <= 1.0e15f)) kmax2 = __uint_as_float(0x7FC00000u);
            if (lane == 0) *(volatile float*)(smem + SM_MISC + 4) = kmax2;
        } else {
            const uint4* gw = (const uint4*)(gate_w + lane * 16);
            const uint4 w0 = __ldg(gw), w1 = __ldg(gw + 1);
            const uint32_t wv[8] = {w0.x, w0.y, w0.z, w0.w, w1.x, w1.y, w1.z, w1.w};
            uint4 xa[6][2];
#pragma unroll
            for (int rr = 0; rr < 6; rr++) {
                const int lr = min(w - 1 + rr * 3, 15);
                const uint4* xp = (const uint4*)(x + (size_t)(blockIdx.x * 16 + lr) * DM + lane * 16);
                xa[rr][0] = __ldg(xp);
                xa[rr][1] = __ldg(xp + 1);
            }
#pragma unroll
            for (int rr = 0; rr < 6; rr++) {
                const uint32_t xv[8] = {xa[rr][0].x, xa[rr][0].y, xa[rr][0].z, xa[rr][0].w, xa[rr][1].x, xa[rr][1].y, xa[rr][1].z, xa[rr][1].w};
                float sum = 0.f;
#pragma unroll
                for (int i = 0; i < 8; i++) {
                    sum += bf_round(bf_lo(xv[i]) * bf_lo(wv[i]));
                    sum += bf_round(bf_hi(xv[i]) * bf_hi(wv[i]));
                }
#pragma unroll
                for (int o = 16; o > 0; o >>= 1) sum += __shfl_xor_sync(0xffffffffu, sum, o);
                if (lane == 0) {
                    sum = bf_round(sum);
                    g_gate[blockIdx.x * 16 + min(w - 1 + rr * 3, 15)] = bf_round(1.f / (1.f + __expf(-sum)));
                }
            }
        }
    }
    __syncthreads();
    if (tid == 384) {
        for (int g = 1; g < 8; g++) {
            mbar_expect_tx(sb + BAR_KV + g * 8, 16384);
            bulk_g2s(sb + g * CHUNK_BYTES, kv_src + g * 16384, 16384, sb + BAR_KV + g * 8);
        }
    }
    __syncwarp();

    {
        uint32_t c3f = 0x3F003F00u;
        asm volatile("" : "+r"(c3f));
        const uint64_t kd0 = make_desc(sb, 4096, 128, 0);
        const uint64_t vd0 = make_desc(sb + 8192, 128, 4096, 0);
#pragma unroll 1
        for (int t = 0; t < 4; t++) {
            uint32_t q[4];
            {
                const unsigned char* qp = smem + SM_Q + (wg * 4 + t) * 2048 + ((tid >> 5) & 3) * 512 + (tid & 31) * 8;
                const uint2 a = *(const uint2*)qp, b = *(const uint2*)(qp + 256);
                q[0] = a.x; q[2] = a.y; q[1] = b.x; q[3] = b.y;
            }
            float o[12];
            float s0[32], s1[32];
            uint32_t p[16];
#pragma unroll
            for (int i = 0; i < 12; i++) o[i] = 0.f;
            fence_regs<12>(o);
            {
                mbar_wait_u(sb + BAR_KV, 0);
                if (t == 0) { ts_min(5); ts_max(21); }
                wg_fence();
                qk_n64(s0, q, kd0);
                wg_commit();
                wg_wait<0>();
                fence_regs<32>(s0);
                uint64_t kd = kd0, vd = vd0;
#define HALF_STEP(SC, SN, KOFF, VOFF)                \
    wg_fence();                                      \
    qk_n64(SN, q, kd + (KOFF));                      \
    wg_commit();                                     \
    exp_half<0>(SC, p, c3f);                         \
    wg_fence();                                      \
    pv_n24(o, p, vd + (VOFF));                       \
    pv_n24(o, p + 4, vd + (VOFF) + 16);              \
    wg_commit();                                     \
    wg_wait<2>();                                    \
    exp_half<8>(SC + 16, p + 8, c3f);                \
    wg_fence();                                      \
    pv_n24(o, p + 8, vd + (VOFF) + 32);              \
    pv_n24(o, p + 12, vd + (VOFF) + 48);             \
    wg_commit();                                     \
    wg_wait<1>();                                    \
    fence_regs<32>(SN);
#pragma unroll 1
                for (uint32_t it = 0; it < 16; it++) {
                    mbar_wait_u(sb + BAR_KV + (((it >> 1) + 1) & 7) * 8, 0);
                    const uint64_t inc = (it & 1) ? 1152 : 128;
                    HALF_STEP(s0, s1, 64, 0)
                    HALF_STEP(s1, s0, inc, 64)
                    kd += inc;
                    vd += inc;
                }
                wg_wait<0>();
                fence_regs<12>(o);
            }
            {
                int tid2;
                asm volatile("mov.u32 %0, %%tid.x;" : "=r"(tid2));
                const int lane = tid2 & 31;
                float n0 = bf_lo(q[0]) * bf_lo(q[0]) + bf_hi(q[0]) * bf_hi(q[0]) + bf_lo(q[2]) * bf_lo(q[2]) + bf_hi(q[2]) * bf_hi(q[2]);
                float n1 = bf_lo(q[1]) * bf_lo(q[1]) + bf_hi(q[1]) * bf_hi(q[1]) + bf_lo(q[3]) * bf_lo(q[3]) + bf_hi(q[3]) * bf_hi(q[3]);
                n0 += __shfl_xor_sync(0xffffffffu, n0, 1);
                n1 += __shfl_xor_sync(0xffffffffu, n1, 1);
                n0 += __shfl_xor_sync(0xffffffffu, n0, 2);
                n1 += __shfl_xor_sync(0xffffffffu, n1, 2);
                const float kmax2 = *(volatile float*)(smem + SM_MISC + 4);
                const bool unsafe = !(n0 * kmax2 <= 3600.f) || !(n1 * kmax2 <= 3600.f);
                uint32_t any_unsafe;
                asm volatile(
                    "{\n.reg .pred p, q;\nsetp.ne.u32 q, %1, 0;\nbar.red.or.pred p, %2, 128, q;\nselp.u32 %0, 1, 0, p;\n}"
                    : "=r"(any_unsafe) : "r"((uint32_t)unsafe), "r"(wg + 1) : "memory");
                if (lane == 0) ((volatile uint32_t*)(smem + SM_MISC + 16))[(tid2 >> 5) * 4 + t] = any_unsafe;
            }
            store_o(o, br, mb, nb, wg * 4 + t);
        }
        __syncwarp();
#pragma unroll 1
        for (int t = 0; t < 4; t++) {
            if (!__any_sync(0xffffffffu, ((volatile uint32_t*)(smem + SM_MISC + 16))[(tid >> 5) * 4 + t])) continue;
            uint32_t q[4];
            {
                const unsigned char* qp = smem + SM_Q + (wg * 4 + t) * 2048 + ((tid >> 5) & 3) * 512 + (tid & 31) * 8;
                const uint2 a = *(const uint2*)qp, b = *(const uint2*)(qp + 256);
                q[0] = a.x; q[2] = a.y; q[1] = b.x; q[3] = b.y;
            }
            float o[12], s0[32];
            uint32_t p[16];
#pragma unroll
            for (int i = 0; i < 12; i++) o[i] = 0.f;
            fence_regs<12>(o);
            attn_tile_slow(q, kd0, vd0, o, s0, p);
            store_o(o, br, mb, nb, wg * 4 + t);
        }
    }
    fence_async();
    asm volatile("bar.sync %0, 128;" ::"r"(wg + 1) : "memory");
    if ((tid & 127) == 0) signal(&g_ctr[2 + mb]);
    __syncthreads();
    ts_min(6); ts_max(22);

    const int orow0 = mb * 128 + (nb >> 2) * 64, ocol0 = (nb & 3) * 128;
    if (wg == 2) {
        if (tid == 288) {
            for (int i = 0; i < 2 * C_STAGES; i++) {
                const int kb = i >> 1, b = i & 1;
                const uint32_t s0 = sb + kb * C_STAGE_BYTES + b * 24576;
                mbar_expect_tx(sb + BAR_CF + i * 8, 24576);
                tma_2d(s0 + 8192, &maps.wo[b], ocol0, kb * 64, sb + BAR_CF + i * 8);
                tma_2d(s0 + 16384, &maps.wo[b], ocol0 + 64, kb * 64, sb + BAR_CF + i * 8);
            }
        }
        if (tid == 256) {
            spin_until(&g_ctr[2 + mb], 32);
            fence_async();
            for (int i = 0; i < 2 * C_STAGES; i++) {
                const int kb = i >> 1, b = i & 1;
                tma_2d(sb + kb * C_STAGE_BYTES + b * 24576, &maps.o, kb * 64, b * SEQ + orow0, sb + BAR_CF + i * 8);
            }
            for (int i = 0; i < 2 * C_STAGES; i++) {
                const int kb = C_STAGES + (i >> 1), b = i & 1;
                const uint32_t s0 = sb + (i >> 1) * C_STAGE_BYTES + b * 24576;
                mbar_wait(sb + BAR_CE + i * 8, 0);
                mbar_expect_tx(sb + BAR_CF + i * 8, 24576);
                tma_2d(s0, &maps.o, kb * 64, b * SEQ + orow0, sb + BAR_CF + i * 8);
                tma_2d(s0 + 8192, &maps.wo[b], ocol0, kb * 64, sb + BAR_CF + i * 8);
                tma_2d(s0 + 16384, &maps.wo[b], ocol0 + 64, kb * 64, sb + BAR_CF + i * 8);
            }
            __threadfence();
            if (atomicAdd(&g_ctr[18], 1u) == 127u) {
                for (int i = 0; i < 19; i++) g_ctr[i] = 0u;
            }
        }
    } else if (wg < 2) {
        const int warp = tid >> 5, lane = tid & 31;
        float acc[64];
#pragma unroll
        for (int i = 0; i < 64; i++) acc[i] = 0.f;
        fence_regs<64>(acc);
        const int r = lane >> 2, c = lane & 3;
        const int lrow = (warp & 3) * 16 + r;
        float g0 = 0.f, g1 = 0.f;
#pragma unroll
        for (int kb = 0; kb < 8; kb++) {
            const int st = kb % C_STAGES;
            const uint32_t s0 = sb + st * C_STAGE_BYTES + wg * 24576;
            mbar_wait_u(sb + BAR_CF + (st * 2 + wg) * 8, kb >= C_STAGES ? 1 : 0);
            if (kb == 0) {
                ts_min(8); ts_max(24);
                g0 = __ldcg(g_gate + orow0 + lrow);
                g1 = __ldcg(g_gate + orow0 + lrow + 8);
            }
            const uint64_t ad = make_desc(s0, 16, 1024, 1);
            const uint64_t bd = make_desc(s0 + 8192, 8192, 1024, 1);
            wg_fence();
#pragma unroll
            for (int kk = 0; kk < 4; kk++) mma_n128_ss(acc, ad + kk * 2, bd + kk * 128);
            wg_commit();
            if (kb >= 1 && kb <= C_STAGES) {
                wg_wait<1>();
                if (lane == 0) mbar_arrive(sb + BAR_CE + ((kb - 1) * 2 + wg) * 8);
            }
        }
        wg_wait<0>();
        fence_regs<64>(acc);
        ts_min(9); ts_max(25);
        if (wg) { g0 = bf_round(1.f - g0); g1 = bf_round(1.f - g1); }
        uint32_t t[32];
#pragma unroll
        for (int j = 0; j < 16; j++) {
            t[2 * j] = pack_bf16(g0 * bf_round(acc[4 * j]), g0 * bf_round(acc[4 * j + 1]));
            t[2 * j + 1] = pack_bf16(g1 * bf_round(acc[4 * j + 2]), g1 * bf_round(acc[4 * j + 3]));
        }
        uint32_t* xch = (uint32_t*)(smem + SM_XCH);
        const int lt = tid & 127;
#pragma unroll
        for (int j = 0; j < 16; j++) xch[(wg * 16 + j) * 128 + lt] = wg ? t[j] : t[16 + j];
        asm volatile("bar.sync 1, 256;" ::: "memory");
        unsigned char* ot = smem + wg * 16384;
#pragma unroll
        for (int j = 0; j < 16; j++) {
            const uint32_t mine = wg ? t[16 + j] : t[j];
            const uint32_t other = xch[((wg ^ 1) * 16 + j) * 128 + lt];
            const uint32_t v = pack_bf16(bf_lo(mine) + bf_lo(other), bf_hi(mine) + bf_hi(other));
            *(uint32_t*)(ot + (lrow + (j & 1) * 8) * 144 + (j >> 1) * 16 + c * 4) = v;
        }
        asm volatile("bar.sync %0, 128;" ::"r"(wg + 2) : "memory");
#pragma unroll
        for (int i = 0; i < 4; i++) {
            const int idx = i * 128 + lt, row = idx >> 3, ch = idx & 7;
            const uint4 v = *(const uint4*)(ot + row * 144 + ch * 16);
            *(uint4*)(out + (size_t)(orow0 + row) * DM + ocol0 + wg * 64 + ch * 8) = v;
        }
        ts_min(10); ts_max(26);
    }
}

typedef CUresult (*EncodeFn)(CUtensorMap*, CUtensorMapDataType, cuuint32_t, void*, const cuuint64_t*, const cuuint64_t*, const cuuint32_t*,
                             const cuuint32_t*, CUtensorMapInterleave, CUtensorMapSwizzle, CUtensorMapL2promotion, CUtensorMapFloatOOBfill);

static void encode_2d(EncodeFn fn, CUtensorMap* m, const void* ptr, uint64_t inner, uint64_t outer, uint32_t box_inner, uint32_t box_outer,
                      CUtensorMapSwizzle swz = CU_TENSOR_MAP_SWIZZLE_128B) {
    cuuint64_t dims[2] = {inner, outer};
    cuuint64_t strides[1] = {inner * 2};
    cuuint32_t box[2] = {box_inner, box_outer};
    cuuint32_t es[2] = {1, 1};
    fn(m, CU_TENSOR_MAP_DATA_TYPE_BFLOAT16, 2, (void*)ptr, dims, strides, box, es, CU_TENSOR_MAP_INTERLEAVE_NONE, swz,
       CU_TENSOR_MAP_L2_PROMOTION_L2_256B, CU_TENSOR_MAP_FLOAT_OOB_FILL_NONE);
}

extern "C" void kernel_launch(void* const* d_in, const int* in_sizes, int n_in, void* d_out, int out_size) {
    (void)in_sizes; (void)n_in; (void)out_size;
    static Maps m;
    static const void* cached[11] = {0};
    static bool attr_done = false;
    bool same = true;
    for (int i = 0; i < 11; i++) same = same && (cached[i] == d_in[i]);
    if (!same || !attr_done) {
        void* fnp = nullptr;
        cudaDriverEntryPointQueryResult qr;
        cudaGetDriverEntryPoint("cuTensorMapEncodeTiled", &fnp, cudaEnableDefault, &qr);
        EncodeFn fn = (EncodeFn)fnp;
        void* po = nullptr;
        cudaGetSymbolAddress(&po, g_O);
        encode_2d(fn, &m.x, d_in[0], DM, SEQ, 64, 128);
        encode_2d(fn, &m.wq[0], d_in[1], DM, DM, 64, 64);
        encode_2d(fn, &m.wq[1], d_in[6], DM, DM, 64, 64);
        encode_2d(fn, &m.wkv[0], d_in[2], 16, DM, 8, 256, CU_TENSOR_MAP_SWIZZLE_NONE);
        encode_2d(fn, &m.wkv[1], d_in[3], 16, DM, 8, 256, CU_TENSOR_MAP_SWIZZLE_NONE);
        encode_2d(fn, &m.wkv[2], d_in[7], 16, DM, 8, 256, CU_TENSOR_MAP_SWIZZLE_NONE);
        encode_2d(fn, &m.wkv[3], d_in[8], 16, DM, 8, 256, CU_TENSOR_MAP_SWIZZLE_NONE);
        encode_2d(fn, &m.o, po, DM, 2 * SEQ, 64, 64);
        encode_2d(fn, &m.wo[0], d_in[4], DM, DM, 64, 64);
        encode_2d(fn, &m.wo[1], d_in[9], DM, DM, 64, 64);
        cudaFuncSetAttribute(fused_kernel, cudaFuncAttributeMaxDynamicSharedMemorySize, SMEM_TOTAL);
        for (int i = 0; i < 11; i++) cached[i] = d_in[i];
        attr_done = true;
    }
    cudaLaunchAttribute at[1];
    at[0].id = cudaLaunchAttributeCooperative;
    at[0].val.cooperative = 1;
    cudaLaunchConfig_t cfg = {};
    cfg.stream = cudaStreamPerThread;
    cfg.attrs = at;
    cfg.numAttrs = 1;
    cfg.gridDim = dim3(128);
    cfg.blockDim = dim3(512);
    cfg.dynamicSmemBytes = SMEM_TOTAL;
    cudaLaunchKernelEx(&cfg, fused_kernel, m, (const bf16*)d_in[0], (const bf16*)d_in[10], (const bf16*)d_in[1], (const bf16*)d_in[6],
                       (const bf16*)d_in[4], (const bf16*)d_in[9], (bf16*)d_out);
}
```

```cpp
#include <cuda_runtime.h>
#include <cuda_bf16.h>
#include <cuda.h>
#include <stdint.h>

typedef __nv_bfloat16 bf16;

#define SEQ 2048
#define DM 512
#define ROWS 65536

__device__ __align__(1024) bf16 g_KV[2 * 4 * SEQ * 8];
__device__ __align__(1024) bf16 g_O[2 * ROWS * 16];
__device__ float g_gate[SEQ];
__device__ __align__(16) float g_nrm[512];
__device__ unsigned int g_ctr[32];

#define ts_min(i)
#define ts_max(i)
__device__ __forceinline__ uint32_t smem_u32(const void* p) { return (uint32_t)__cvta_generic_to_shared(p); }
__device__ __forceinline__ uint64_t make_desc(uint32_t saddr, uint32_t lbo, uint32_t sbo, uint32_t swz) {
    uint64_t d = 0;
    d |= (uint64_t)((saddr & 0x3FFFF) >> 4);
    d |= (uint64_t)((lbo & 0x3FFFF) >> 4) << 16;
    d |= (uint64_t)((sbo & 0x3FFFF) >> 4) << 32;
    d |= (uint64_t)swz << 62;
    return d;
}
__device__ __forceinline__ void wg_fence() { asm volatile("wgmma.fence.sync.aligned;" ::: "memory"); }
__device__ __forceinline__ void wg_commit() { asm volatile("wgmma.commit_group.sync.aligned;" ::: "memory"); }
template <int N> __device__ __forceinline__ void wg_wait() { asm volatile("wgmma.wait_group.sync.aligned %0;" ::"n"(N) : "memory"); }
template <int N> __device__ __forceinline__ void fence_regs(float* d) {
#pragma unroll
    for (int i = 0; i < N; i++) asm volatile("" : "+f"(d[i])::"memory");
}
__device__ __forceinline__ void mbar_init(uint32_t bar, uint32_t cnt) { asm volatile("mbarrier.init.shared::cta.b64 [%0], %1;" ::"r"(bar), "r"(cnt)); }
__device__ __forceinline__ void mbar_expect_tx(uint32_t bar, uint32_t bytes) {
    asm volatile("mbarrier.arrive.expect_tx.shared::cta.b64 _, [%0], %1;" ::"r"(bar), "r"(bytes) : "memory");
}
__device__ __forceinline__ void mbar_arrive(uint32_t bar) { asm volatile("mbarrier.arrive.shared::cta.b64 _, [%0];" ::"r"(bar) : "memory"); }
__device__ __forceinline__ void mbar_wait(uint32_t bar, uint32_t parity) {
    asm volatile(
        "{\n.reg .pred p;\n"
        "WAIT_LOOP:\n"
        "mbarrier.try_wait.parity.shared::cta.b64 p, [%0], %1;\n"
        "@p bra DONE;\n"
        "bra WAIT_LOOP;\n"
        "DONE:\n}" ::"r"(bar), "r"(parity) : "memory");
}
__device__ __forceinline__ void mbar_wait_u(uint32_t bar, uint32_t parity) {
    uint32_t ok;
    do {
        asm volatile(
            "{\n.reg .pred p;\nmbarrier.try_wait.parity.shared::cta.b64 p, [%1], %2;\nselp.u32 %0, 1, 0, p;\n}"
            : "=r"(ok) : "r"(bar), "r"(parity) : "memory");
    } while (!__all_sync(0xffffffffu, ok));
}
__device__ __forceinline__ void bulk_g2s(uint32_t dst, const void* src, uint32_t bytes, uint32_t bar) {
    asm volatile("cp.async.bulk.shared::cluster.global.mbarrier::complete_tx::bytes [%0], [%1], %2, [%3];" ::"r"(dst), "l"(src), "r"(bytes), "r"(bar) : "memory");
}
__device__ __forceinline__ void tma_2d(uint32_t dst, const CUtensorMap* map, int c0, int c1, uint32_t bar) {
    asm volatile("cp.async.bulk.tensor.2d.shared::cluster.global.mbarrier::complete_tx::bytes [%0], [%1, {%3, %4}], [%2];" ::"r"(dst), "l"(map), "r"(bar), "r"(c0), "r"(c1) : "memory");
}
__device__ __forceinline__ void tma_2d_mc(uint32_t dst, const CUtensorMap* map, int c0, int c1, uint32_t bar, uint16_t mask) {
    asm volatile("cp.async.bulk.tensor.2d.shared::cluster.global.mbarrier::complete_tx::bytes.multicast::cluster [%0], [%1, {%3, %4}], [%2], %5;"
                 ::"r"(dst), "l"(map), "r"(bar), "r"(c0), "r"(c1), "h"(mask) : "memory");
}
__device__ __forceinline__ void cluster_sync() {
    asm volatile("barrier.cluster.arrive.aligned;\nbarrier.cluster.wait.aligned;" ::: "memory");
}
__device__ __forceinline__ void l2_prefetch(const void* p, uint32_t bytes) {
    asm volatile("cp.async.bulk.prefetch.L2.global [%0], %1;" ::"l"(p), "r"(bytes) : "memory");
}
__device__ __forceinline__ void pdl_launch() { asm volatile("griddepcontrol.launch_dependents;" ::: "memory"); }
__device__ __forceinline__ void pdl_wait() { asm volatile("griddepcontrol.wait;" ::: "memory"); }
__device__ __forceinline__ void fence_async() { asm volatile("fence.proxy.async;" ::: "memory"); }
__device__ __forceinline__ uint32_t pack_bf16(float lo, float hi) {
    uint32_t r;
    asm("cvt.rn.bf16x2.f32 %0, %1, %2;" : "=r"(r) : "f"(hi), "f"(lo));
    return r;
}
__device__ __forceinline__ float bf_lo(uint32_t u) { return __uint_as_float(u << 16); }
__device__ __forceinline__ float bf_hi(uint32_t u) { return __uint_as_float(u & 0xFFFF0000u); }
__device__ __forceinline__ float bf_round(float x) { return __bfloat162float(__float2bfloat16_rn(x)); }

#define A8(b) "+f"(d[b + 0]), "+f"(d[b + 1]), "+f"(d[b + 2]), "+f"(d[b + 3]), "+f"(d[b + 4]), "+f"(d[b + 5]), "+f"(d[b + 6]), "+f"(d[b + 7])
#define W8(b) "=f"(d[b + 0]), "=f"(d[b + 1]), "=f"(d[b + 2]), "=f"(d[b + 3]), "=f"(d[b + 4]), "=f"(d[b + 5]), "=f"(d[b + 6]), "=f"(d[b + 7])

__device__ __forceinline__ void mma_n8_ss(float* d, uint64_t ad, uint64_t bd) {
    asm volatile("wgmma.mma_async.sync.aligned.m64n8k16.f32.bf16.bf16 {%0,%1,%2,%3}, %4, %5, 1, 1, 1, 0, 1;"
                 : "+f"(d[0]), "+f"(d[1]), "+f"(d[2]), "+f"(d[3])
                 : "l"(ad), "l"(bd));
}
__device__ __forceinline__ void mma_n128_ss(float* d, uint64_t ad, uint64_t bd) {
    asm volatile(
        "wgmma.mma_async.sync.aligned.m64n128k16.f32.bf16.bf16 "
        "{%0,%1,%2,%3,%4,%5,%6,%7,%8,%9,%10,%11,%12,%13,%14,%15,%16,%17,%18,%19,%20,%21,%22,%23,%24,%25,%26,%27,%28,%29,%30,%31,"
        "%32,%33,%34,%35,%36,%37,%38,%39,%40,%41,%42,%43,%44,%45,%46,%47,%48,%49,%50,%51,%52,%53,%54,%55,%56,%57,%58,%59,%60,%61,%62,%63}, "
        "%64, %65, 1, 1, 1, 0, 1;"
        : A8(0), A8(8), A8(16), A8(24), A8(32), A8(40), A8(48), A8(56)
        : "l"(ad), "l"(bd));
}
__device__ __forceinline__ void qk_n64(float* d, const uint32_t* a, uint64_t bd) {
    asm volatile(
        "wgmma.mma_async.sync.aligned.m64n64k16.f32.bf16.bf16 "
        "{%0,%1,%2,%3,%4,%5,%6,%7,%8,%9,%10,%11,%12,%13,%14,%15,%16,%17,%18,%19,%20,%21,%22,%23,%24,%25,%26,%27,%28,%29,%30,%31}, "
        "{%32,%33,%34,%35}, %36, 0, 1, 1, 0;"
        : W8(0), W8(8), W8(16), W8(24)
        : "r"(a[0]), "r"(a[1]), "r"(a[2]), "r"(a[3]), "l"(bd));
}
__device__ __forceinline__ void pv_n24(float* d, const uint32_t* a, uint64_t bd) {
    asm volatile(
        "wgmma.mma_async.sync.aligned.m64n24k16.f32.bf16.bf16 {%0,%1,%2,%3,%4,%5,%6,%7,%8,%9,%10,%11}, {%12,%13,%14,%15}, %16, 1, 1, 1, 1;"
        : A8(0), "+f"(d[8]), "+f"(d[9]), "+f"(d[10]), "+f"(d[11])
        : "r"(a[0]), "r"(a[1]), "r"(a[2]), "r"(a[3]), "l"(bd));
}

__device__ __forceinline__ float ex2(float x) {
    float e;
    asm("ex2.approx.ftz.f32 %0, %1;" : "=f"(e) : "f"(x));
    return e;
}
__device__ __forceinline__ uint32_t exp_pair_mufu(float x0, float x1) { return pack_bf16(ex2(x0), ex2(x1)); }

#define MAGIC0 (98304.0f + 127.0f - 75.0f / 128.0f)
#define MAGIC1 (98304.0f + 127.0f - 75.0f / 128.0f - 143.5f)
template <int PRM>
__device__ __forceinline__ uint32_t exp_pair_poly(float x0, float x1, uint32_t c3f) {
    float t0 = x0 + MAGIC0;
    float t1 = x1 + (PRM ? MAGIC0 : MAGIC1);
    uint32_t L, y2, E, r;
    if (PRM)
        asm("prmt.b32 %0, %1, %2, 0x5410;" : "=r"(L) : "r"(__float_as_uint(t0)), "r"(__float_as_uint(t1)));
    else
        L = __float_as_uint(t1) * 65536u + __float_as_uint(t0);
    asm("lop3.b32 %0, %1, 0x007F007F, %2, 0xEA;" : "=r"(y2) : "r"(L), "r"(c3f));
    E = L & 0x7F807F80u;
    asm("fma.rn.bf16x2 %0, %1, %2, %3;" : "=r"(r) : "r"(L), "r"(y2), "r"(E));
    return r;
}
#define EXP_MASK 0x4949u
template <int BASE>
__device__ __forceinline__ void exp_half(const float* s, uint32_t* p, uint32_t c3f) {
#pragma unroll
    for (int i = 0; i < 8; i++) {
        if ((EXP_MASK >> (BASE + i)) & 1) p[i] = exp_pair_mufu(s[2 * i], s[2 * i + 1]);
        else if (i & 1) p[i] = exp_pair_poly<1>(s[2 * i], s[2 * i + 1], c3f);
        else p[i] = exp_pair_poly<0>(s[2 * i], s[2 * i + 1], c3f);
    }
}

struct Maps {
    CUtensorMap x;
    CUtensorMap wq[2];
    CUtensorMap wkv[4];
    CUtensorMap o;
    CUtensorMap wo[2];
};
#define SM_X 20480
#define SM_WKV 151552
#define SM_WQ 159744
#define CHUNK_BYTES 20480
#define SM_Q 163840
#define C_STAGES 4
#define C_STAGE_BYTES 49152
#define SM_XCH 196608
#define SM_BAR 225280
#define BAR_X (SM_BAR)
#define BAR_KV (SM_BAR + 64)
#define BAR_CF (SM_BAR + 128)
#define BAR_CE (SM_BAR + 192)
#define BAR_WF (SM_BAR + 256)
#define BAR_WE (SM_BAR + 288)
#define BAR_WKV (SM_BAR + 320)
#define SM_MISC (SM_BAR + 384)
#define SMEM_TOTAL (SM_BAR + 1024 + 1024)

__device__ __forceinline__ void spin_until(const unsigned int* ctr, unsigned int target) {
    unsigned int v;
    for (unsigned int it = 0; it < (1u << 26); it++) {
        asm volatile("ld.acquire.gpu.global.u32 %0, [%1];" : "=r"(v) : "l"(ctr) : "memory");
        if (v >= target) return;
    }
    __trap();
}
__device__ __forceinline__ void signal(unsigned int* ctr) {
    asm volatile("red.release.gpu.global.add.u32 [%0], 1;" ::"l"(ctr) : "memory");
}

__device__ __forceinline__ void attn_tile_slow(const uint32_t* qq, uint64_t kd0, uint64_t vd0, float* o, float* s, uint32_t* p) {
    float m0 = -INFINITY, m1 = -INFINITY;
#pragma unroll 1
    for (int ch = 0; ch < 32; ch++) {
        wg_fence();
        qk_n64(s, qq, kd0 + (uint64_t)((ch >> 2) * 1280 + (ch & 3) * 64));
        wg_commit();
        wg_wait<0>();
        fence_regs<32>(s);
#pragma unroll
        for (int j = 0; j < 8; j++) {
            m0 = fmaxf(m0, fmaxf(s[4 * j], s[4 * j + 1]));
            m1 = fmaxf(m1, fmaxf(s[4 * j + 2], s[4 * j + 3]));
        }
    }
    m0 = fmaxf(m0, __shfl_xor_sync(0xffffffffu, m0, 1));
    m1 = fmaxf(m1, __shfl_xor_sync(0xffffffffu, m1, 1));
    m0 = fmaxf(m0, __shfl_xor_sync(0xffffffffu, m0, 2));
    m1 = fmaxf(m1, __shfl_xor_sync(0xffffffffu, m1, 2));
#pragma unroll 1
    for (int ch = 0; ch < 32; ch++) {
        wg_fence();
        qk_n64(s, qq, kd0 + (uint64_t)((ch >> 2) * 1280 + (ch & 3) * 64));
        wg_commit();
        wg_wait<0>();
        fence_regs<32>(s);
#pragma unroll
        for (int j = 0; j < 8; j++) {
            p[2 * j] = exp_pair_mufu(s[4 * j] - m0, s[4 * j + 1] - m0);
            p[2 * j + 1] = exp_pair_mufu(s[4 * j + 2] - m1, s[4 * j + 3] - m1);
        }
        wg_fence();
#pragma unroll
        for (int j = 0; j < 4; j++) pv_n24(o, p + 4 * j, vd0 + (uint64_t)((ch >> 2) * 1280 + (ch & 3) * 64 + 16 * j));
        wg_commit();
        wg_wait<0>();
        fence_regs<12>(o);
    }
}

__device__ __forceinline__ void store_o(const float* o, int br, int mb, int nb, int tile) {
    int tid2;
    asm volatile("mov.u32 %0, %%tid.x;" : "=r"(tid2));
    const int lane = tid2 & 31;
    const float l0 = __shfl_sync(0xffffffffu, o[8], lane & ~3);
    const float l1 = __shfl_sync(0xffffffffu, o[10], lane & ~3);
    const float i0 = 1.f / l0, i1 = 1.f / l1;
    const uint32_t row = (uint32_t)(br * SEQ + mb * 128 + (tile & 1) * 64 + ((tid2 >> 5) & 3) * 16 + (lane >> 2));
    bf16* op = g_O + row * DM + ((nb & 3) * 8 + (tile >> 1)) * 16 + (lane & 3) * 2;
    *(uint32_t*)(op) = pack_bf16(o[0] * i0, o[1] * i0);
    *(uint32_t*)(op + 8 * DM) = pack_bf16(o[2] * i1, o[3] * i1);
    *(uint32_t*)(op + 8) = pack_bf16(o[4] * i0, o[5] * i0);
    *(uint32_t*)(op + 8 * DM + 8) = pack_bf16(o[6] * i1, o[7] * i1);
}

__global__ void __launch_bounds__(512, 1) fused_kernel(const __grid_constant__ Maps maps, const bf16* __restrict__ x, const bf16* __restrict__ gate_w,
                                                        const bf16* __restrict__ wqa, const bf16* __restrict__ wqb, const bf16* __restrict__ woa,
                                                        const bf16* __restrict__ wob, bf16* __restrict__ out) {
    extern __shared__ unsigned char smem_raw[];
    const uint32_t sb = (smem_u32(smem_raw) + 1023) & ~1023u;
    unsigned char* smem = smem_raw + (sb - smem_u32(smem_raw));
    const int tid = threadIdx.x;
    const int wg = __shfl_sync(0xffffffffu, tid >> 7, 0);
    const int mb = blockIdx.x >> 3, nb = blockIdx.x & 7;
    const int br = nb >> 2;
    ts_min(0); ts_max(16);
    if (tid == 0) {
        for (int i = 0; i < 8; i++) {
            mbar_init(sb + BAR_X + i * 8, 1);
            mbar_init(sb + BAR_KV + i * 8, 1);
            mbar_init(sb + BAR_CF + i * 8, 1);
            mbar_init(sb + BAR_CE + i * 8, 4);
        }
        for (int i = 0; i < 4; i++) {
            mbar_init(sb + BAR_WF + i * 8, 1);
            mbar_init(sb + BAR_WE + i * 8, 8);
        }
        mbar_init(sb + BAR_WKV, 1);
        *(unsigned int*)(smem + SM_MISC) = 0u;
        asm volatile("fence.mbarrier_init.release.cluster;" ::: "memory");
    }
    if (tid == 416) {
        l2_prefetch(x + (size_t)blockIdx.x * 8192, 16384);
        l2_prefetch(wqa + (size_t)blockIdx.x * 2048, 4096);
        l2_prefetch(wqb + (size_t)blockIdx.x * 2048, 4096);
    }
    cluster_sync();

    const unsigned char* kv_src = (const unsigned char*)g_KV + (size_t)br * 131072;
    if (wg < 2) {
        const int warp = tid >> 5, lane = tid & 31;
        float acc[64];
#pragma unroll
        for (int i = 0; i < 64; i++) acc[i] = 0.f;
        fence_regs<64>(acc);
#pragma unroll
        for (int kb = 0; kb < 8; kb++) {
            const int st = kb & 3;
            mbar_wait_u(sb + BAR_X + kb * 8, 0);
            mbar_wait_u(sb + BAR_WF + st * 8, kb >> 2);
            if (kb == 0) { ts_min(12); ts_max(28); }
            const uint64_t ad = make_desc(sb + SM_X + kb * 16384 + wg * 8192, 16, 1024, 1);
            const uint64_t bd = make_desc(sb + SM_WQ + st * 16384, 8192, 1024, 1);
            wg_fence();
#pragma unroll
            for (int kk = 0; kk < 4; kk++) mma_n128_ss(acc, ad + kk * 2, bd + kk * 128);
            wg_commit();
            if (kb >= 1 && kb <= 4) {
                wg_wait<1>();
                if (lane == 0) mbar_arrive(sb + BAR_WE + (kb - 1) * 8);
            }
        }
        wg_wait<0>();
        fence_regs<64>(acc);
        ts_min(1); ts_max(17);
        asm volatile("bar.sync 1, 384;" ::: "memory");
        const int r = lane >> 2, c = lane & 3;
        const float qs = 0.25f * 1.4426950408889634f;
        unsigned char* qp = smem + SM_Q + wg * 2048 + ((warp & 3) * 16 + r) * 32 + c * 8;
#pragma unroll
        for (int h = 0; h < 8; h++) {
            const float* a = acc + h * 8;
            *(uint2*)(qp + h * 4096) = make_uint2(pack_bf16(a[0] * qs, a[1] * qs), pack_bf16(a[4] * qs, a[5] * qs));
            *(uint2*)(qp + h * 4096 + 256) = make_uint2(pack_bf16(a[2] * qs, a[3] * qs), pack_bf16(a[6] * qs, a[7] * qs));
        }
        ts_min(2); ts_max(18);
    } else if (wg == 2) {
        const int warp = (tid >> 5) & 3, lane = tid & 31;
        float a0[4] = {0.f, 0.f, 0.f, 0.f}, a1[4] = {0.f, 0.f, 0.f, 0.f};
        fence_regs<4>(a0);
        fence_regs<4>(a1);
        *(uint4*)(smem + 16384 + (tid & 127) * 16) = make_uint4(0x00003F80u, 0, 0, 0);
        *(uint4*)(smem + 18432 + (tid & 127) * 16) = make_uint4(0x00003F80u, 0, 0, 0);
        mbar_wait_u(sb + BAR_WKV, 0);
#pragma unroll
        for (int kb = 0; kb < 8; kb++) {
            mbar_wait_u(sb + BAR_X + kb * 8, 0);
            const uint64_t ad = make_desc(sb + SM_X + kb * 16384, 16, 1024, 1);
            const uint64_t bd = make_desc(sb + SM_WKV + kb * 1024, 128, 128, 0);
            wg_fence();
#pragma unroll
            for (int kk = 0; kk < 4; kk++) {
                mma_n8_ss(a0, ad + kk * 2, bd + kk * 16);
                mma_n8_ss(a1, ad + 512 + kk * 2, bd + kk * 16);
            }
            wg_commit();
        }
        wg_wait<0>();
        fence_regs<4>(a0);
        fence_regs<4>(a1);
        ts_min(14); ts_max(30);
        const int r = lane >> 2, c = lane & 3;
        const int row = mb * 128 + warp * 16 + r;
        const uint32_t k0 = pack_bf16(a0[0], a0[1]), k1 = pack_bf16(a0[2], a0[3]);
        const uint32_t k2 = pack_bf16(a1[0], a1[1]), k3 = pack_bf16(a1[2], a1[3]);
        bf16* kvp = g_KV + (size_t)br * 65536 + (row >> 8) * 8192 + (nb & 3) * 2048 + (row & 255) * 8 + 2 * c;
        *(uint32_t*)kvp = k0;
        *(uint32_t*)(kvp + 64) = k1;
        *(uint32_t*)(kvp + 512) = k2;
        *(uint32_t*)(kvp + 576) = k3;
        unsigned int mu;
        if (((nb >> 1) & 1) == 0) {
            float n0 = bf_lo(k0) * bf_lo(k0) + bf_hi(k0) * bf_hi(k0);
            float n1 = bf_lo(k1) * bf_lo(k1) + bf_hi(k1) * bf_hi(k1);
            float n2 = bf_lo(k2) * bf_lo(k2) + bf_hi(k2) * bf_hi(k2);
            float n3 = bf_lo(k3) * bf_lo(k3) + bf_hi(k3) * bf_hi(k3);
#pragma unroll
            for (int sft = 1; sft <= 2; sft <<= 1) {
                n0 += __shfl_xor_sync(0xffffffffu, n0, sft);
                n1 += __shfl_xor_sync(0xffffffffu, n1, sft);
                n2 += __shfl_xor_sync(0xffffffffu, n2, sft);
                n3 += __shfl_xor_sync(0xffffffffu, n3, sft);
            }
            mu = max(max(__float_as_uint(n0), __float_as_uint(n1)), max(__float_as_uint(n2), __float_as_uint(n3)));
        } else {
            mu = max(max(max((k0 << 16) & 0x7FFFFFFFu, k0 & 0x7FFF0000u), max((k1 << 16) & 0x7FFFFFFFu, k1 & 0x7FFF0000u)),
                     max(max((k2 << 16) & 0x7FFFFFFFu, k2 & 0x7FFF0000u), max((k3 << 16) & 0x7FFFFFFFu, k3 & 0x7FFF0000u)));
        }
        mu = __reduce_max_sync(0xffffffffu, mu);
        asm volatile("fence.proxy.async.global;" ::: "memory");
        __syncwarp();
        if (lane == 0) {
            g_nrm[(nb * 16 + mb) * 4 + warp] = __uint_as_float(mu);
            signal(&g_ctr[br]);
            ts_min(13); ts_max(29);
        }
        asm volatile("bar.sync 1, 384;" ::: "memory");
#pragma unroll
        for (int i = 1; i < 8; i++) {
            *(uint4*)(smem + i * CHUNK_BYTES + 16384 + (tid & 127) * 16) = make_uint4(0x00003F80u, 0, 0, 0);
            *(uint4*)(smem + i * CHUNK_BYTES + 18432 + (tid & 127) * 16) = make_uint4(0x00003F80u, 0, 0, 0);
        }
        asm volatile("fence.proxy.async.shared::cta;" ::: "memory");
    } else {
        const int lane = tid & 31, w = (tid >> 5) & 3;
        if (w == 0) {
            if (lane == 0) {
                mbar_expect_tx(sb + BAR_WKV, 8192);
                tma_2d(sb + SM_WKV, &maps.wkv[nb >> 1], (nb & 1) * 8, 0, sb + BAR_WKV);
                tma_2d(sb + SM_WKV + 4096, &maps.wkv[nb >> 1], (nb & 1) * 8, 256, sb + BAR_WKV);
                for (int kb = 0; kb < 8; kb++) {
                    mbar_expect_tx(sb + BAR_X + kb * 8, 16384);
                    if ((kb & 1) == (nb & 1)) tma_2d_mc(sb + SM_X + kb * 16384, &maps.x, kb * 64, mb * 128, sb + BAR_X + kb * 8, 3);
                }
                mbar_wait(sb + BAR_X + 48, 0);
                mbar_wait(sb + BAR_X + 56, 0);
                ts_min(11); ts_max(27);
                for (int st = 0; st < 4; st++) {
                    mbar_expect_tx(sb + BAR_WF + st * 8, 16384);
                    tma_2d(sb + SM_WQ + st * 16384, &maps.wq[br], (nb & 3) * 128, st * 64, sb + BAR_WF + st * 8);
                    tma_2d(sb + SM_WQ + st * 16384 + 8192, &maps.wq[br], (nb & 3) * 128 + 64, st * 64, sb + BAR_WF + st * 8);
                }
                for (int st = 0; st < 4; st++) {
                    mbar_wait(sb + BAR_WE + st * 8, 0);
                    mbar_expect_tx(sb + BAR_WF + st * 8, 16384);
                    tma_2d(sb + SM_WQ + st * 16384, &maps.wq[br], (nb & 3) * 128, (st + 4) * 64, sb + BAR_WF + st * 8);
                    tma_2d(sb + SM_WQ + st * 16384 + 8192, &maps.wq[br], (nb & 3) * 128 + 64, (st + 4) * 64, sb + BAR_WF + st * 8);
                }
                l2_prefetch(woa + (size_t)blockIdx.x * 2048, 4096);
                l2_prefetch(wob + (size_t)blockIdx.x * 2048, 4096);
                spin_until(&g_ctr[br], 256);
                fence_async();
                ts_min(4); ts_max(20);
                mbar_expect_tx(sb + BAR_KV, 16384);
                bulk_g2s(sb, kv_src, 16384, sb + BAR_KV);
            }
            __syncwarp();
            const uint4 hk = __ldcg((const uint4*)g_nrm + br * 64 + lane);
            const uint4 hv = __ldcg((const uint4*)g_nrm + br * 64 + 32 + lane);
            unsigned int h = max(max(hk.x, hk.y), max(hk.z, hk.w));
            const unsigned int nv = max(max(hv.x, hv.y), max(hv.z, hv.w));
#pragma unroll
            for (int sft = 8; sft > 0; sft >>= 1) h = max(h, __shfl_xor_sync(0xffffffffu, h, sft));
            float kmax2 = __uint_as_float(h) + __uint_as_float(__shfl_xor_sync(0xffffffffu, h, 16));
            const float vmax = __uint_as_float(__reduce_max_sync(0xffffffffu, nv));
            if (!(vmax <= 1.0e15f)) kmax2 = __uint_as_float(0x7FC00000u);
            if (lane == 0) *(volatile float*)(smem + SM_MISC + 4) = kmax2;
        } else {
            const uint4* gw = (const uint4*)(gate_w + lane * 16);
            const uint4 w0 = __ldg(gw), w1 = __ldg(gw + 1);
            const uint32_t wv[8] = {w0.x, w0.y, w0.z, w0.w, w1.x, w1.y, w1.z, w1.w};
            uint4 xa[6][2];
#pragma unroll
            for (int rr = 0; rr < 6; rr++) {
                const int lr = min(w - 1 + rr * 3, 15);
                const uint4* xp = (const uint4*)(x + (size_t)(blockIdx.x * 16 + lr) * DM + lane * 16);
                xa[rr][0] = __ldg(xp);
                xa[rr][1] = __ldg(xp + 1);
            }
#pragma unroll
            for (int rr = 0; rr < 6; rr++) {
                const uint32_t xv[8] = {xa[rr][0].x, xa[rr][0].y, xa[rr][0].z, xa[rr][0].w, xa[rr][1].x, xa[rr][1].y, xa[rr][1].z, xa[rr][1].w};
                float sum = 0.f;
#pragma unroll
                for (int i = 0; i < 8; i++) {
                    sum += bf_round(bf_lo(xv[i]) * bf_lo(wv[i]));
                    sum += bf_round(bf_hi(xv[i]) * bf_hi(wv[i]));
                }
#pragma unroll
                for (int o = 16; o > 0; o >>= 1) sum += __shfl_xor_sync(0xffffffffu, sum, o);
                if (lane == 0) {
                    sum = bf_round(sum);
                    g_gate[blockIdx.x * 16 + min(w - 1 + rr * 3, 15)] = bf_round(1.f / (1.f + __expf(-sum)));
                }
            }
        }
    }
    __syncthreads();
    if (tid == 384) {
        for (int g = 1; g < 8; g++) {
            mbar_expect_tx(sb + BAR_KV + g * 8, 16384);
            bulk_g2s(sb + g * CHUNK_BYTES, kv_src + g * 16384, 16384, sb + BAR_KV + g * 8);
        }
    }
    __syncwarp();

    {
        uint32_t c3f = 0x3F003F00u;
        asm volatile("" : "+r"(c3f));
        const uint64_t kd0 = make_desc(sb, 4096, 128, 0);
        const uint64_t vd0 = make_desc(sb + 8192, 128, 4096, 0);
#pragma unroll 1
        for (int t = 0; t < 4; t++) {
            uint32_t q[4];
            {
                const unsigned char* qp = smem + SM_Q + (wg * 4 + t) * 2048 + ((tid >> 5) & 3) * 512 + (tid & 31) * 8;
                const uint2 a = *(const uint2*)qp, b = *(const uint2*)(qp + 256);
                q[0] = a.x; q[2] = a.y; q[1] = b.x; q[3] = b.y;
            }
            float o[12];
            float s0[32], s1[32];
            uint32_t p[16];
#pragma unroll
            for (int i = 0; i < 12; i++) o[i] = 0.f;
            fence_regs<12>(o);
            {
                mbar_wait_u(sb + BAR_KV, 0);
                if (t == 0) { ts_min(5); ts_max(21); }
                wg_fence();
                qk_n64(s0, q, kd0);
                wg_commit();
                wg_wait<0>();
                fence_regs<32>(s0);
                uint64_t kd = kd0, vd = vd0;
#define HALF_STEP(SC, SN, KOFF, VOFF)                \
    wg_fence();                                      \
    qk_n64(SN, q, kd + (KOFF));                      \
    wg_commit();                                     \
    exp_half<0>(SC, p, c3f);                         \
    wg_fence();                                      \
    pv_n24(o, p, vd + (VOFF));                       \
    pv_n24(o, p + 4, vd + (VOFF) + 16);              \
    wg_commit();                                     \
    wg_wait<2>();                                    \
    exp_half<8>(SC + 16, p + 8, c3f);                \
    wg_fence();                                      \
    pv_n24(o, p + 8, vd + (VOFF) + 32);              \
    pv_n24(o, p + 12, vd + (VOFF) + 48);             \
    wg_commit();                                     \
    wg_wait<1>();                                    \
    fence_regs<32>(SN);
#pragma unroll 1
                for (uint32_t it = 0; it < 16; it++) {
                    mbar_wait_u(sb + BAR_KV + (((it >> 1) + 1) & 7) * 8, 0);
                    const uint64_t inc = (it & 1) ? 1152 : 128;
                    HALF_STEP(s0, s1, 64, 0)
                    HALF_STEP(s1, s0, inc, 64)
                    kd += inc;
                    vd += inc;
                }
                wg_wait<0>();
                fence_regs<12>(o);
            }
            {
                int tid2;
                asm volatile("mov.u32 %0, %%tid.x;" : "=r"(tid2));
                const int lane = tid2 & 31;
                float n0 = bf_lo(q[0]) * bf_lo(q[0]) + bf_hi(q[0]) * bf_hi(q[0]) + bf_lo(q[2]) * bf_lo(q[2]) + bf_hi(q[2]) * bf_hi(q[2]);
                float n1 = bf_lo(q[1]) * bf_lo(q[1]) + bf_hi(q[1]) * bf_hi(q[1]) + bf_lo(q[3]) * bf_lo(q[3]) + bf_hi(q[3]) * bf_hi(q[3]);
                n0 += __shfl_xor_sync(0xffffffffu, n0, 1);
                n1 += __shfl_xor_sync(0xffffffffu, n1, 1);
                n0 += __shfl_xor_sync(0xffffffffu, n0, 2);
                n1 += __shfl_xor_sync(0xffffffffu, n1, 2);
                const float kmax2 = *(volatile float*)(smem + SM_MISC + 4);
                const bool unsafe = !(n0 * kmax2 <= 3600.f) || !(n1 * kmax2 <= 3600.f);
                uint32_t any_unsafe;
                asm volatile(
                    "{\n.reg .pred p, q;\nsetp.ne.u32 q, %1, 0;\nbar.red.or.pred p, %2, 128, q;\nselp.u32 %0, 1, 0, p;\n}"
                    : "=r"(any_unsafe) : "r"((uint32_t)unsafe), "r"(wg + 1) : "memory");
                if (lane == 0) ((volatile uint32_t*)(smem + SM_MISC + 16))[(tid2 >> 5) * 4 + t] = any_unsafe;
            }
            store_o(o, br, mb, nb, wg * 4 + t);
        }
        __syncwarp();
#pragma unroll 1
        for (int t = 0; t < 4; t++) {
            if (!__any_sync(0xffffffffu, ((volatile uint32_t*)(smem + SM_MISC + 16))[(tid >> 5) * 4 + t])) continue;
            uint32_t q[4];
            {
                const unsigned char* qp = smem + SM_Q + (wg * 4 + t) * 2048 + ((tid >> 5) & 3) * 512 + (tid & 31) * 8;
                const uint2 a = *(const uint2*)qp, b = *(const uint2*)(qp + 256);
                q[0] = a.x; q[2] = a.y; q[1] = b.x; q[3] = b.y;
            }
            float o[12], s0[32];
            uint32_t p[16];
#pragma unroll
            for (int i = 0; i < 12; i++) o[i] = 0.f;
            fence_regs<12>(o);
            attn_tile_slow(q, kd0, vd0, o, s0, p);
            store_o(o, br, mb, nb, wg * 4 + t);
        }
    }
    fence_async();
    asm volatile("bar.sync %0, 128;" ::"r"(wg + 1) : "memory");
    if ((tid & 127) == 0) signal(&g_ctr[2 + mb]);
    __syncthreads();
    ts_min(6); ts_max(22);

    const int orow0 = mb * 128 + (nb >> 2) * 64, ocol0 = (nb & 3) * 128;
    if (wg == 2) {
        if (tid == 288) {
            for (int i = 0; i < 2 * C_STAGES; i++) {
                const int kb = i >> 1, b = i & 1;
                const uint32_t s0 = sb + kb * C_STAGE_BYTES + b * 24576;
                mbar_expect_tx(sb + BAR_CF + i * 8, 24576);
                tma_2d(s0 + 8192, &maps.wo[b], ocol0, kb * 64, sb + BAR_CF + i * 8);
                tma_2d(s0 + 16384, &maps.wo[b], ocol0 + 64, kb * 64, sb + BAR_CF + i * 8);
            }
        }
        if (tid == 256) {
            spin_until(&g_ctr[2 + mb], 32);
            fence_async();
            for (int i = 0; i < 2 * C_STAGES; i++) {
                const int kb = i >> 1, b = i & 1;
                tma_2d(sb + kb * C_STAGE_BYTES + b * 24576, &maps.o, kb * 64, b * SEQ + orow0, sb + BAR_CF + i * 8);
            }
            for (int i = 0; i < 2 * C_STAGES; i++) {
                const int kb = C_STAGES + (i >> 1), b = i & 1;
                const uint32_t s0 = sb + (i >> 1) * C_STAGE_BYTES + b * 24576;
                mbar_wait(sb + BAR_CE + i * 8, 0);
                mbar_expect_tx(sb + BAR_CF + i * 8, 24576);
                tma_2d(s0, &maps.o, kb * 64, b * SEQ + orow0, sb + BAR_CF + i * 8);
                tma_2d(s0 + 8192, &maps.wo[b], ocol0, kb * 64, sb + BAR_CF + i * 8);
                tma_2d(s0 + 16384, &maps.wo[b], ocol0 + 64, kb * 64, sb + BAR_CF + i * 8);
            }
            __threadfence();
            if (atomicAdd(&g_ctr[18], 1u) == 127u) {
                for (int i = 0; i < 19; i++) g_ctr[i] = 0u;
            }
        }
    } else if (wg < 2) {
        const int warp = tid >> 5, lane = tid & 31;
        float acc[64];
#pragma unroll
        for (int i = 0; i < 64; i++) acc[i] = 0.f;
        fence_regs<64>(acc);
        const int r = lane >> 2, c = lane & 3;
        const int lrow = (warp & 3) * 16 + r;
        float g0 = 0.f, g1 = 0.f;
#pragma unroll
        for (int kb = 0; kb < 8; kb++) {
            const int st = kb % C_STAGES;
            const uint32_t s0 = sb + st * C_STAGE_BYTES + wg * 24576;
            mbar_wait_u(sb + BAR_CF + (st * 2 + wg) * 8, kb >= C_STAGES ? 1 : 0);
            if (kb == 0) {
                ts_min(8); ts_max(24);
                g0 = __ldcg(g_gate + orow0 + lrow);
                g1 = __ldcg(g_gate + orow0 + lrow + 8);
            }
            const uint64_t ad = make_desc(s0, 16, 1024, 1);
            const uint64_t bd = make_desc(s0 + 8192, 8192, 1024, 1);
            wg_fence();
#pragma unroll
            for (int kk = 0; kk < 4; kk++) mma_n128_ss(acc, ad + kk * 2, bd + kk * 128);
            wg_commit();
            if (kb >= 1 && kb <= C_STAGES) {
                wg_wait<1>();
                if (lane == 0) mbar_arrive(sb + BAR_CE + ((kb - 1) * 2 + wg) * 8);
            }
        }
        wg_wait<0>();
        fence_regs<64>(acc);
        ts_min(9); ts_max(25);
        if (wg) { g0 = bf_round(1.f - g0); g1 = bf_round(1.f - g1); }
        uint32_t t[32];
#pragma unroll
        for (int j = 0; j < 16; j++) {
            t[2 * j] = pack_bf16(g0 * bf_round(acc[4 * j]), g0 * bf_round(acc[4 * j + 1]));
            t[2 * j + 1] = pack_bf16(g1 * bf_round(acc[4 * j + 2]), g1 * bf_round(acc[4 * j + 3]));
        }
        uint32_t* xch = (uint32_t*)(smem + SM_XCH);
        const int lt = tid & 127;
#pragma unroll
        for (int j = 0; j < 16; j++) xch[(wg * 16 + j) * 128 + lt] = wg ? t[j] : t[16 + j];
        asm volatile("bar.sync 1, 256;" ::: "memory");
        unsigned char* ot = smem + wg * 16384;
#pragma unroll
        for (int j = 0; j < 16; j++) {
            const uint32_t mine = wg ? t[16 + j] : t[j];
            const uint32_t other = xch[((wg ^ 1) * 16 + j) * 128 + lt];
            const uint32_t v = pack_bf16(bf_lo(mine) + bf_lo(other), bf_hi(mine) + bf_hi(other));
            *(uint32_t*)(ot + (lrow + (j & 1) * 8) * 144 + (j >> 1) * 16 + c * 4) = v;
        }
        asm volatile("bar.sync %0, 128;" ::"r"(wg + 2) : "memory");
#pragma unroll
        for (int i = 0; i < 4; i++) {
            const int idx = i * 128 + lt, row = idx >> 3, ch = idx & 7;
            const uint4 v = *(const uint4*)(ot + row * 144 + ch * 16);
            *(uint4*)(out + (size_t)(orow0 + row) * DM + ocol0 + wg * 64 + ch * 8) = v;
        }
        ts_min(10); ts_max(26);
    }
}

typedef CUresult (*EncodeFn)(CUtensorMap*, CUtensorMapDataType, cuuint32_t, void*, const cuuint64_t*, const cuuint64_t*, const cuuint32_t*,
                             const cuuint32_t*, CUtensorMapInterleave, CUtensorMapSwizzle, CUtensorMapL2promotion, CUtensorMapFloatOOBfill);

static void encode_2d(EncodeFn fn, CUtensorMap* m, const void* ptr, uint64_t inner, uint64_t outer, uint32_t box_inner, uint32_t box_outer,
                      CUtensorMapSwizzle swz = CU_TENSOR_MAP_SWIZZLE_128B) {
    cuuint64_t dims[2] = {inner, outer};
    cuuint64_t strides[1] = {inner * 2};
    cuuint32_t box[2] = {box_inner, box_outer};
    cuuint32_t es[2] = {1, 1};
    fn(m, CU_TENSOR_MAP_DATA_TYPE_BFLOAT16, 2, (void*)ptr, dims, strides, box, es, CU_TENSOR_MAP_INTERLEAVE_NONE, swz,
       CU_TENSOR_MAP_L2_PROMOTION_L2_256B, CU_TENSOR_MAP_FLOAT_OOB_FILL_NONE);
}

extern "C" void kernel_launch(void* const* d_in, const int* in_sizes, int n_in, void* d_out, int out_size) {
    (void)in_sizes; (void)n_in; (void)out_size;
    static Maps m;
    static const void* cached[11] = {0};
    static bool attr_done = false;
    bool same = true;
    for (int i = 0; i < 11; i++) same = same && (cached[i] == d_in[i]);
    if (!same || !attr_done) {
        void* fnp = nullptr;
        cudaDriverEntryPointQueryResult qr;
        cudaGetDriverEntryPoint("cuTensorMapEncodeTiled", &fnp, cudaEnableDefault, &qr);
        EncodeFn fn = (EncodeFn)fnp;
        void* po = nullptr;
        cudaGetSymbolAddress(&po, g_O);
        encode_2d(fn, &m.x, d_in[0], DM, SEQ, 64, 128);
        encode_2d(fn, &m.wq[0], d_in[1], DM, DM, 64, 64);
        encode_2d(fn, &m.wq[1], d_in[6], DM, DM, 64, 64);
        encode_2d(fn, &m.wkv[0], d_in[2], 16, DM, 8, 256, CU_TENSOR_MAP_SWIZZLE_NONE);
        encode_2d(fn, &m.wkv[1], d_in[3], 16, DM, 8, 256, CU_TENSOR_MAP_SWIZZLE_NONE);
        encode_2d(fn, &m.wkv[2], d_in[7], 16, DM, 8, 256, CU_TENSOR_MAP_SWIZZLE_NONE);
        encode_2d(fn, &m.wkv[3], d_in[8], 16, DM, 8, 256, CU_TENSOR_MAP_SWIZZLE_NONE);
        encode_2d(fn, &m.o, po, DM, 2 * SEQ, 64, 64);
        encode_2d(fn, &m.wo[0], d_in[4], DM, DM, 64, 64);
        encode_2d(fn, &m.wo[1], d_in[9], DM, DM, 64, 64);
        cudaFuncSetAttribute(fused_kernel, cudaFuncAttributeMaxDynamicSharedMemorySize, SMEM_TOTAL);
        for (int i = 0; i < 11; i++) cached[i] = d_in[i];
        attr_done = true;
    }
    cudaLaunchAttribute at[2];
    at[1].id = cudaLaunchAttributeClusterDimension;
    at[1].val.clusterDim.x = 2;
    at[1].val.clusterDim.y = 1;
    at[1].val.clusterDim.z = 1;
    at[0].id = cudaLaunchAttributeCooperative;
    at[0].val.cooperative = 1;
    cudaLaunchConfig_t cfg = {};
    cfg.stream = cudaStreamPerThread;
    cfg.attrs = at;
    cfg.numAttrs = 2;
    cfg.gridDim = dim3(128);
    cfg.blockDim = dim3(512);
    cfg.dynamicSmemBytes = SMEM_TOTAL;
    cudaLaunchKernelEx(&cfg, fused_kernel, m, (const bf16*)d_in[0], (const bf16*)d_in[10], (const bf16*)d_in[1], (const bf16*)d_in[6],
                       (const bf16*)d_in[4], (const bf16*)d_in[9], (bf16*)d_out);
}
```

```cpp
#include <cuda_runtime.h>
#include <cuda_bf16.h>
#include <cuda.h>
#include <stdint.h>

typedef __nv_bfloat16 bf16;

#define SEQ 2048
#define DM 512
#define ROWS 65536

__device__ __align__(1024) bf16 g_KV[2 * 4 * SEQ * 8];
__device__ __align__(1024) bf16 g_O[2 * ROWS * 16];
__device__ float g_gate[SEQ];
__device__ __align__(16) float g_nrm[512];
__device__ unsigned int g_ctr[32];

#define ts_min(i)
#define ts_max(i)
__device__ __forceinline__ uint32_t smem_u32(const void* p) { return (uint32_t)__cvta_generic_to_shared(p); }
__device__ __forceinline__ uint64_t make_desc(uint32_t saddr, uint32_t lbo, uint32_t sbo, uint32_t swz) {
    uint64_t d = 0;
    d |= (uint64_t)((saddr & 0x3FFFF) >> 4);
    d |= (uint64_t)((lbo & 0x3FFFF) >> 4) << 16;
    d |= (uint64_t)((sbo & 0x3FFFF) >> 4) << 32;
    d |= (uint64_t)swz << 62;
    return d;
}
__device__ __forceinline__ void wg_fence() { asm volatile("wgmma.fence.sync.aligned;" ::: "memory"); }
__device__ __forceinline__ void wg_commit() { asm volatile("wgmma.commit_group.sync.aligned;" ::: "memory"); }
template <int N> __device__ __forceinline__ void wg_wait() { asm volatile("wgmma.wait_group.sync.aligned %0;" ::"n"(N) : "memory"); }
template <int N> __device__ __forceinline__ void fence_regs(float* d) {
#pragma unroll
    for (int i = 0; i < N; i++) asm volatile("" : "+f"(d[i])::"memory");
}
__device__ __forceinline__ void mbar_init(uint32_t bar, uint32_t cnt) { asm volatile("mbarrier.init.shared::cta.b64 [%0], %1;" ::"r"(bar), "r"(cnt)); }
__device__ __forceinline__ void mbar_expect_tx(uint32_t bar, uint32_t bytes) {
    asm volatile("mbarrier.arrive.expect_tx.shared::cta.b64 _, [%0], %1;" ::"r"(bar), "r"(bytes) : "memory");
}
__device__ __forceinline__ void mbar_arrive(uint32_t bar) { asm volatile("mbarrier.arrive.shared::cta.b64 _, [%0];" ::"r"(bar) : "memory"); }
__device__ __forceinline__ void mbar_wait(uint32_t bar, uint32_t parity) {
    asm volatile(
        "{\n.reg .pred p;\n"
        "WAIT_LOOP:\n"
        "mbarrier.try_wait.parity.shared::cta.b64 p, [%0], %1;\n"
        "@p bra DONE;\n"
        "bra WAIT_LOOP;\n"
        "DONE:\n}" ::"r"(bar), "r"(parity) : "memory");
}
__device__ __forceinline__ void mbar_wait_u(uint32_t bar, uint32_t parity) {
    uint32_t ok;
    do {
        asm volatile(
            "{\n.reg .pred p;\nmbarrier.try_wait.parity.shared::cta.b64 p, [%1], %2;\nselp.u32 %0, 1, 0, p;\n}"
            : "=r"(ok) : "r"(bar), "r"(parity) : "memory");
    } while (!__all_sync(0xffffffffu, ok));
}
__device__ __forceinline__ void bulk_g2s(uint32_t dst, const void* src, uint32_t bytes, uint32_t bar) {
    asm volatile("cp.async.bulk.shared::cluster.global.mbarrier::complete_tx::bytes [%0], [%1], %2, [%3];" ::"r"(dst), "l"(src), "r"(bytes), "r"(bar) : "memory");
}
__device__ __forceinline__ void tma_2d(uint32_t dst, const CUtensorMap* map, int c0, int c1, uint32_t bar) {
    asm volatile("cp.async.bulk.tensor.2d.shared::cluster.global.mbarrier::complete_tx::bytes [%0], [%1, {%3, %4}], [%2];" ::"r"(dst), "l"(map), "r"(bar), "r"(c0), "r"(c1) : "memory");
}
__device__ __forceinline__ void l2_prefetch(const void* p, uint32_t bytes) {
    asm volatile("cp.async.bulk.prefetch.L2.global [%0], %1;" ::"l"(p), "r"(bytes) : "memory");
}
__device__ __forceinline__ void pdl_launch() { asm volatile("griddepcontrol.launch_dependents;" ::: "memory"); }
__device__ __forceinline__ void pdl_wait() { asm volatile("griddepcontrol.wait;" ::: "memory"); }
__device__ __forceinline__ void fence_async() { asm volatile("fence.proxy.async;" ::: "memory"); }
__device__ __forceinline__ uint32_t pack_bf16(float lo, float hi) {
    uint32_t r;
    asm("cvt.rn.bf16x2.f32 %0, %1, %2;" : "=r"(r) : "f"(hi), "f"(lo));
    return r;
}
__device__ __forceinline__ float bf_lo(uint32_t u) { return __uint_as_float(u << 16); }
__device__ __forceinline__ float bf_hi(uint32_t u) { return __uint_as_float(u & 0xFFFF0000u); }
__device__ __forceinline__ float bf_round(float x) { return __bfloat162float(__float2bfloat16_rn(x)); }

#define A8(b) "+f"(d[b + 0]), "+f"(d[b + 1]), "+f"(d[b + 2]), "+f"(d[b + 3]), "+f"(d[b + 4]), "+f"(d[b + 5]), "+f"(d[b + 6]), "+f"(d[b + 7])
#define W8(b) "=f"(d[b + 0]), "=f"(d[b + 1]), "=f"(d[b + 2]), "=f"(d[b + 3]), "=f"(d[b + 4]), "=f"(d[b + 5]), "=f"(d[b + 6]), "=f"(d[b + 7])

__device__ __forceinline__ void mma_n8_ss(float* d, uint64_t ad, uint64_t bd) {
    asm volatile("wgmma.mma_async.sync.aligned.m64n8k16.f32.bf16.bf16 {%0,%1,%2,%3}, %4, %5, 1, 1, 1, 0, 1;"
                 : "+f"(d[0]), "+f"(d[1]), "+f"(d[2]), "+f"(d[3])
                 : "l"(ad), "l"(bd));
}
__device__ __forceinline__ void mma_n128_ss(float* d, uint64_t ad, uint64_t bd) {
    asm volatile(
        "wgmma.mma_async.sync.aligned.m64n128k16.f32.bf16.bf16 "
        "{%0,%1,%2,%3,%4,%5,%6,%7,%8,%9,%10,%11,%12,%13,%14,%15,%16,%17,%18,%19,%20,%21,%22,%23,%24,%25,%26,%27,%28,%29,%30,%31,"
        "%32,%33,%34,%35,%36,%37,%38,%39,%40,%41,%42,%43,%44,%45,%46,%47,%48,%49,%50,%51,%52,%53,%54,%55,%56,%57,%58,%59,%60,%61,%62,%63}, "
        "%64, %65, 1, 1, 1, 0, 1;"
        : A8(0), A8(8), A8(16), A8(24), A8(32), A8(40), A8(48), A8(56)
        : "l"(ad), "l"(bd));
}
__device__ __forceinline__ void qk_n64(float* d, const uint32_t* a, uint64_t bd) {
    asm volatile(
        "wgmma.mma_async.sync.aligned.m64n64k16.f32.bf16.bf16 "
        "{%0,%1,%2,%3,%4,%5,%6,%7,%8,%9,%10,%11,%12,%13,%14,%15,%16,%17,%18,%19,%20,%21,%22,%23,%24,%25,%26,%27,%28,%29,%30,%31}, "
        "{%32,%33,%34,%35}, %36, 0, 1, 1, 0;"
        : W8(0), W8(8), W8(16), W8(24)
        : "r"(a[0]), "r"(a[1]), "r"(a[2]), "r"(a[3]), "l"(bd));
}
__device__ __forceinline__ void pv_n24(float* d, const uint32_t* a, uint64_t bd) {
    asm volatile(
        "wgmma.mma_async.sync.aligned.m64n24k16.f32.bf16.bf16 {%0,%1,%2,%3,%4,%5,%6,%7,%8,%9,%10,%11}, {%12,%13,%14,%15}, %16, 1, 1, 1, 1;"
        : A8(0), "+f"(d[8]), "+f"(d[9]), "+f"(d[10]), "+f"(d[11])
        : "r"(a[0]), "r"(a[1]), "r"(a[2]), "r"(a[3]), "l"(bd));
}

__device__ __forceinline__ float ex2(float x) {
    float e;
    asm("ex2.approx.ftz.f32 %0, %1;" : "=f"(e) : "f"(x));
    return e;
}
__device__ __forceinline__ uint32_t exp_pair_mufu(float x0, float x1) { return pack_bf16(ex2(x0), ex2(x1)); }

#define MAGIC0 (98304.0f + 127.0f - 75.0f / 128.0f)
#define MAGIC1 (98304.0f + 127.0f - 75.0f / 128.0f - 143.5f)
template <int PRM>
__device__ __forceinline__ uint32_t exp_pair_poly(float x0, float x1, uint32_t c3f) {
    float t0 = x0 + MAGIC0;
    float t1 = x1 + (PRM ? MAGIC0 : MAGIC1);
    uint32_t L, y2, E, r;
    if (PRM)
        asm("prmt.b32 %0, %1, %2, 0x5410;" : "=r"(L) : "r"(__float_as_uint(t0)), "r"(__float_as_uint(t1)));
    else
        L = __float_as_uint(t1) * 65536u + __float_as_uint(t0);
    asm("lop3.b32 %0, %1, 0x007F007F, %2, 0xEA;" : "=r"(y2) : "r"(L), "r"(c3f));
    E = L & 0x7F807F80u;
    asm("fma.rn.bf16x2 %0, %1, %2, %3;" : "=r"(r) : "r"(L), "r"(y2), "r"(E));
    return r;
}
#define EXP_MASK 0x5454u
template <int BASE>
__device__ __forceinline__ void exp_half(const float* s, uint32_t* p, uint32_t c3f) {
#pragma unroll
    for (int i = 0; i < 8; i++) {
        if ((EXP_MASK >> (BASE + i)) & 1) p[i] = exp_pair_mufu(s[2 * i], s[2 * i + 1]);
        else p[i] = exp_pair_poly<0>(s[2 * i], s[2 * i + 1], c3f);
    }
}

struct Maps {
    CUtensorMap x;
    CUtensorMap wq[2];
    CUtensorMap wkv[4];
    CUtensorMap o;
    CUtensorMap wo[2];
};
#define SM_X 20480
#define SM_WKV 151552
#define SM_WQ 159744
#define CHUNK_BYTES 20480
#define SM_Q 163840
#define C_STAGES 4
#define C_STAGE_BYTES 49152
#define SM_XCH 196608
#define SM_BAR 225280
#define BAR_X (SM_BAR)
#define BAR_KV (SM_BAR + 64)
#define BAR_CF (SM_BAR + 128)
#define BAR_CE (SM_BAR + 192)
#define BAR_WF (SM_BAR + 256)
#define BAR_WE (SM_BAR + 288)
#define BAR_WKV (SM_BAR + 320)
#define SM_MISC (SM_BAR + 384)
#define SMEM_TOTAL (SM_BAR + 1024 + 1024)

__device__ __forceinline__ void spin_until(const unsigned int* ctr, unsigned int target) {
    unsigned int v;
    for (unsigned int it = 0; it < (1u << 26); it++) {
        asm volatile("ld.acquire.gpu.global.u32 %0, [%1];" : "=r"(v) : "l"(ctr) : "memory");
        if (v >= target) return;
    }
    __trap();
}
__device__ __forceinline__ void signal(unsigned int* ctr) {
    asm volatile("red.release.gpu.global.add.u32 [%0], 1;" ::"l"(ctr) : "memory");
}

__device__ __forceinline__ void attn_tile_slow(const uint32_t* qq, uint64_t kd0, uint64_t vd0, float* o, float* s, uint32_t* p) {
    float m0 = -INFINITY, m1 = -INFINITY;
#pragma unroll 1
    for (int ch = 0; ch < 32; ch++) {
        wg_fence();
        qk_n64(s, qq, kd0 + (uint64_t)((ch >> 2) * 1280 + (ch & 3) * 64));
        wg_commit();
        wg_wait<0>();
        fence_regs<32>(s);
#pragma unroll
        for (int j = 0; j < 8; j++) {
            m0 = fmaxf(m0, fmaxf(s[4 * j], s[4 * j + 1]));
            m1 = fmaxf(m1, fmaxf(s[4 * j + 2], s[4 * j + 3]));
        }
    }
    m0 = fmaxf(m0, __shfl_xor_sync(0xffffffffu, m0, 1));
    m1 = fmaxf(m1, __shfl_xor_sync(0xffffffffu, m1, 1));
    m0 = fmaxf(m0, __shfl_xor_sync(0xffffffffu, m0, 2));
    m1 = fmaxf(m1, __shfl_xor_sync(0xffffffffu, m1, 2));
#pragma unroll 1
    for (int ch = 0; ch < 32; ch++) {
        wg_fence();
        qk_n64(s, qq, kd0 + (uint64_t)((ch >> 2) * 1280 + (ch & 3) * 64));
        wg_commit();
        wg_wait<0>();
        fence_regs<32>(s);
#pragma unroll
        for (int j = 0; j < 8; j++) {
            p[2 * j] = exp_pair_mufu(s[4 * j] - m0, s[4 * j + 1] - m0);
            p[2 * j + 1] = exp_pair_mufu(s[4 * j + 2] - m1, s[4 * j + 3] - m1);
        }
        wg_fence();
#pragma unroll
        for (int j = 0; j < 4; j++) pv_n24(o, p + 4 * j, vd0 + (uint64_t)((ch >> 2) * 1280 + (ch & 3) * 64 + 16 * j));
        wg_commit();
        wg_wait<0>();
        fence_regs<12>(o);
    }
}

__device__ __forceinline__ void store_o(const float* o, int br, int mb, int nb, int tile) {
    int tid2;
    asm volatile("mov.u32 %0, %%tid.x;" : "=r"(tid2));
    const int lane = tid2 & 31;
    const float l0 = __shfl_sync(0xffffffffu, o[8], lane & ~3);
    const float l1 = __shfl_sync(0xffffffffu, o[10], lane & ~3);
    const float i0 = 1.f / l0, i1 = 1.f / l1;
    const uint32_t row = (uint32_t)(br * SEQ + mb * 128 + (tile & 1) * 64 + ((tid2 >> 5) & 3) * 16 + (lane >> 2));
    bf16* op = g_O + row * DM + ((nb & 3) * 8 + (tile >> 1)) * 16 + (lane & 3) * 2;
    *(uint32_t*)(op) = pack_bf16(o[0] * i0, o[1] * i0);
    *(uint32_t*)(op + 8 * DM) = pack_bf16(o[2] * i1, o[3] * i1);
    *(uint32_t*)(op + 8) = pack_bf16(o[4] * i0, o[5] * i0);
    *(uint32_t*)(op + 8 * DM + 8) = pack_bf16(o[6] * i1, o[7] * i1);
}

__global__ void __launch_bounds__(512, 1) fused_kernel(const __grid_constant__ Maps maps, const bf16* __restrict__ x, const bf16* __restrict__ gate_w,
                                                        const bf16* __restrict__ wqa, const bf16* __restrict__ wqb, const bf16* __restrict__ woa,
                                                        const bf16* __restrict__ wob, bf16* __restrict__ out) {
    extern __shared__ unsigned char smem_raw[];
    const uint32_t sb = (smem_u32(smem_raw) + 1023) & ~1023u;
    unsigned char* smem = smem_raw + (sb - smem_u32(smem_raw));
    const int tid = threadIdx.x;
    const int wg = __shfl_sync(0xffffffffu, tid >> 7, 0);
    const int mb = blockIdx.x >> 3, nb = blockIdx.x & 7;
    const int br = nb >> 2;
    ts_min(0); ts_max(16);
    if (tid == 384) {
        for (int i = 0; i < 8; i++) mbar_init(sb + BAR_X + i * 8, 1);
        mbar_init(sb + BAR_WKV, 1);
        asm volatile("fence.mbarrier_init.release.cluster;" ::: "memory");
        mbar_expect_tx(sb + BAR_WKV, 8192);
        tma_2d(sb + SM_WKV, &maps.wkv[nb >> 1], (nb & 1) * 8, 0, sb + BAR_WKV);
        tma_2d(sb + SM_WKV + 4096, &maps.wkv[nb >> 1], (nb & 1) * 8, 256, sb + BAR_WKV);
        for (int kb = 0; kb < 8; kb++) {
            mbar_expect_tx(sb + BAR_X + kb * 8, 16384);
            tma_2d(sb + SM_X + kb * 16384, &maps.x, kb * 64, mb * 128, sb + BAR_X + kb * 8);
        }
    }
    if (tid == 352) asm volatile("prefetch.tensormap [%0];" ::"l"(&maps.x) : "memory");
    if (tid == 0) {
        for (int i = 0; i < 8; i++) {
            mbar_init(sb + BAR_KV + i * 8, 1);
            mbar_init(sb + BAR_CF + i * 8, 1);
            mbar_init(sb + BAR_CE + i * 8, 4);
        }
        for (int i = 0; i < 4; i++) {
            mbar_init(sb + BAR_WF + i * 8, 1);
            mbar_init(sb + BAR_WE + i * 8, 8);
        }
        asm volatile("fence.mbarrier_init.release.cluster;" ::: "memory");
    }
    if (tid == 416) {
        l2_prefetch(wqa + (size_t)blockIdx.x * 2048, 4096);
        l2_prefetch(wqb + (size_t)blockIdx.x * 2048, 4096);
        asm volatile("prefetch.tensormap [%0];" ::"l"(&maps.wq[br]) : "memory");
        asm volatile("prefetch.tensormap [%0];" ::"l"(&maps.o) : "memory");
        asm volatile("prefetch.tensormap [%0];" ::"l"(&maps.wo[0]) : "memory");
        asm volatile("prefetch.tensormap [%0];" ::"l"(&maps.wo[1]) : "memory");
    }
    __syncthreads();

    const unsigned char* kv_src = (const unsigned char*)g_KV + (size_t)br * 131072;
    if (wg < 2) {
        const int warp = tid >> 5, lane = tid & 31;
        float acc[64];
#pragma unroll
        for (int i = 0; i < 64; i++) acc[i] = 0.f;
        fence_regs<64>(acc);
        asm volatile("bar.sync 3, 384;" ::: "memory");
#pragma unroll
        for (int kb = 0; kb < 8; kb++) {
            const int st = kb & 3;
            mbar_wait_u(sb + BAR_WF + st * 8, kb >> 2);
            if (kb == 0) { ts_min(12); ts_max(28); }
            const uint64_t ad = make_desc(sb + SM_X + kb * 16384 + wg * 8192, 16, 1024, 1);
            const uint64_t bd = make_desc(sb + SM_WQ + st * 16384, 8192, 1024, 1);
            wg_fence();
#pragma unroll
            for (int kk = 0; kk < 4; kk++) mma_n128_ss(acc, ad + kk * 2, bd + kk * 128);
            wg_commit();
            if (kb >= 1 && kb <= 4) {
                wg_wait<1>();
                if (lane == 0) mbar_arrive(sb + BAR_WE + (kb - 1) * 8);
            }
        }
        wg_wait<0>();
        fence_regs<64>(acc);
        ts_min(1); ts_max(17);
        asm volatile("bar.sync 1, 384;" ::: "memory");
        const int r = lane >> 2, c = lane & 3;
        const float qs = 0.25f * 1.4426950408889634f;
        unsigned char* qp = smem + SM_Q + wg * 2048 + ((warp & 3) * 16 + r) * 32 + c * 8;
#pragma unroll
        for (int h = 0; h < 8; h++) {
            const float* a = acc + h * 8;
            *(uint2*)(qp + h * 4096) = make_uint2(pack_bf16(a[0] * qs, a[1] * qs), pack_bf16(a[4] * qs, a[5] * qs));
            *(uint2*)(qp + h * 4096 + 256) = make_uint2(pack_bf16(a[2] * qs, a[3] * qs), pack_bf16(a[6] * qs, a[7] * qs));
        }
        ts_min(2); ts_max(18);
    } else if (wg == 2) {
        const int warp = (tid >> 5) & 3, lane = tid & 31;
        float a0[4] = {0.f, 0.f, 0.f, 0.f}, a1[4] = {0.f, 0.f, 0.f, 0.f};
        fence_regs<4>(a0);
        fence_regs<4>(a1);
        *(uint4*)(smem + 16384 + (tid & 127) * 16) = make_uint4(0x00003F80u, 0, 0, 0);
        *(uint4*)(smem + 18432 + (tid & 127) * 16) = make_uint4(0x00003F80u, 0, 0, 0);
        mbar_wait_u(sb + BAR_WKV, 0);
#pragma unroll
        for (int kb = 0; kb < 8; kb++) {
            mbar_wait_u(sb + BAR_X + kb * 8, 0);
            const uint64_t ad = make_desc(sb + SM_X + kb * 16384, 16, 1024, 1);
            const uint64_t bd = make_desc(sb + SM_WKV + kb * 1024, 128, 128, 0);
            wg_fence();
#pragma unroll
            for (int kk = 0; kk < 4; kk++) {
                mma_n8_ss(a0, ad + kk * 2, bd + kk * 16);
                mma_n8_ss(a1, ad + 512 + kk * 2, bd + kk * 16);
            }
            wg_commit();
        }
        wg_wait<0>();
        fence_regs<4>(a0);
        fence_regs<4>(a1);
        asm volatile("bar.arrive 3, 384;" ::: "memory");
        ts_min(14); ts_max(30);
        const int r = lane >> 2, c = lane & 3;
        const int row = mb * 128 + warp * 16 + r;
        const uint32_t k0 = pack_bf16(a0[0], a0[1]), k1 = pack_bf16(a0[2], a0[3]);
        const uint32_t k2 = pack_bf16(a1[0], a1[1]), k3 = pack_bf16(a1[2], a1[3]);
        bf16* kvp = g_KV + (size_t)br * 65536 + (row >> 8) * 8192 + (nb & 3) * 2048 + (row & 255) * 8 + 2 * c;
        *(uint32_t*)kvp = k0;
        *(uint32_t*)(kvp + 64) = k1;
        *(uint32_t*)(kvp + 512) = k2;
        *(uint32_t*)(kvp + 576) = k3;
        unsigned int mu;
        if (((nb >> 1) & 1) == 0) {
            float n0 = bf_lo(k0) * bf_lo(k0) + bf_hi(k0) * bf_hi(k0);
            float n1 = bf_lo(k1) * bf_lo(k1) + bf_hi(k1) * bf_hi(k1);
            float n2 = bf_lo(k2) * bf_lo(k2) + bf_hi(k2) * bf_hi(k2);
            float n3 = bf_lo(k3) * bf_lo(k3) + bf_hi(k3) * bf_hi(k3);
#pragma unroll
            for (int sft = 1; sft <= 2; sft <<= 1) {
                n0 += __shfl_xor_sync(0xffffffffu, n0, sft);
                n1 += __shfl_xor_sync(0xffffffffu, n1, sft);
                n2 += __shfl_xor_sync(0xffffffffu, n2, sft);
                n3 += __shfl_xor_sync(0xffffffffu, n3, sft);
            }
            mu = max(max(__float_as_uint(n0), __float_as_uint(n1)), max(__float_as_uint(n2), __float_as_uint(n3)));
        } else {
            mu = max(max(max((k0 << 16) & 0x7FFFFFFFu, k0 & 0x7FFF0000u), max((k1 << 16) & 0x7FFFFFFFu, k1 & 0x7FFF0000u)),
                     max(max((k2 << 16) & 0x7FFFFFFFu, k2 & 0x7FFF0000u), max((k3 << 16) & 0x7FFFFFFFu, k3 & 0x7FFF0000u)));
        }
        mu = __reduce_max_sync(0xffffffffu, mu);
        asm volatile("fence.proxy.async.global;" ::: "memory");
        __syncwarp();
        if (lane == 0) {
            g_nrm[(nb * 16 + mb) * 4 + warp] = __uint_as_float(mu);
            signal(&g_ctr[br]);
            ts_min(13); ts_max(29);
        }
        asm volatile("bar.sync 1, 384;" ::: "memory");
#pragma unroll
        for (int i = 1; i < 8; i++) {
            *(uint4*)(smem + i * CHUNK_BYTES + 16384 + (tid & 127) * 16) = make_uint4(0x00003F80u, 0, 0, 0);
            *(uint4*)(smem + i * CHUNK_BYTES + 18432 + (tid & 127) * 16) = make_uint4(0x00003F80u, 0, 0, 0);
        }
        asm volatile("fence.proxy.async.shared::cta;" ::: "memory");
    } else {
        const int lane = tid & 31, w = (tid >> 5) & 3;
        if (w == 0) {
            if (lane == 0) {
                mbar_wait(sb + BAR_X + 56, 0);
                ts_min(11); ts_max(27);
                for (int st = 0; st < 4; st++) {
                    mbar_expect_tx(sb + BAR_WF + st * 8, 16384);
                    tma_2d(sb + SM_WQ + st * 16384, &maps.wq[br], (nb & 3) * 128, st * 64, sb + BAR_WF + st * 8);
                    tma_2d(sb + SM_WQ + st * 16384 + 8192, &maps.wq[br], (nb & 3) * 128 + 64, st * 64, sb + BAR_WF + st * 8);
                }
                for (int st = 0; st < 4; st++) {
                    mbar_wait(sb + BAR_WE + st * 8, 0);
                    mbar_expect_tx(sb + BAR_WF + st * 8, 16384);
                    tma_2d(sb + SM_WQ + st * 16384, &maps.wq[br], (nb & 3) * 128, (st + 4) * 64, sb + BAR_WF + st * 8);
                    tma_2d(sb + SM_WQ + st * 16384 + 8192, &maps.wq[br], (nb & 3) * 128 + 64, (st + 4) * 64, sb + BAR_WF + st * 8);
                }
                l2_prefetch(woa + (size_t)blockIdx.x * 2048, 4096);
                l2_prefetch(wob + (size_t)blockIdx.x * 2048, 4096);
                spin_until(&g_ctr[br], 256);
                fence_async();
                ts_min(4); ts_max(20);
                mbar_expect_tx(sb + BAR_KV, 16384);
                bulk_g2s(sb, kv_src, 16384, sb + BAR_KV);
            }
            __syncwarp();
            const uint4 hk = __ldcg((const uint4*)g_nrm + br * 64 + lane);
            const uint4 hv = __ldcg((const uint4*)g_nrm + br * 64 + 32 + lane);
            unsigned int h = max(max(hk.x, hk.y), max(hk.z, hk.w));
            const unsigned int nv = max(max(hv.x, hv.y), max(hv.z, hv.w));
#pragma unroll
            for (int sft = 8; sft > 0; sft >>= 1) h = max(h, __shfl_xor_sync(0xffffffffu, h, sft));
            float kmax2 = __uint_as_float(h) + __uint_as_float(__shfl_xor_sync(0xffffffffu, h, 16));
            const float vmax = __uint_as_float(__reduce_max_sync(0xffffffffu, nv));
            if (!(vmax <= 1.0e15f)) kmax2 = __uint_as_float(0x7FC00000u);
            if (lane == 0) *(volatile float*)(smem + SM_MISC + 4) = kmax2;
        } else {
            const uint4* gw = (const uint4*)(gate_w + lane * 16);
            const uint4 w0 = __ldg(gw), w1 = __ldg(gw + 1);
            const uint32_t wv[8] = {w0.x, w0.y, w0.z, w0.w, w1.x, w1.y, w1.z, w1.w};
            uint4 xa[6][2];
#pragma unroll
            for (int rr = 0; rr < 6; rr++) {
                const int lr = min(w - 1 + rr * 3, 15);
                const uint4* xp = (const uint4*)(x + (size_t)(blockIdx.x * 16 + lr) * DM + lane * 16);
                xa[rr][0] = __ldg(xp);
                xa[rr][1] = __ldg(xp + 1);
            }
#pragma unroll
            for (int rr = 0; rr < 6; rr++) {
                const uint32_t xv[8] = {xa[rr][0].x, xa[rr][0].y, xa[rr][0].z, xa[rr][0].w, xa[rr][1].x, xa[rr][1].y, xa[rr][1].z, xa[rr][1].w};
                float sum = 0.f;
#pragma unroll
                for (int i = 0; i < 8; i++) {
                    sum += bf_round(bf_lo(xv[i]) * bf_lo(wv[i]));
                    sum += bf_round(bf_hi(xv[i]) * bf_hi(wv[i]));
                }
#pragma unroll
                for (int o = 16; o > 0; o >>= 1) sum += __shfl_xor_sync(0xffffffffu, sum, o);
                if (lane == 0) {
                    sum = bf_round(sum);
                    g_gate[blockIdx.x * 16 + min(w - 1 + rr * 3, 15)] = bf_round(1.f / (1.f + __expf(-sum)));
                }
            }
        }
    }
    __syncthreads();
    if (tid == 384) {
        for (int g = 1; g < 8; g++) {
            mbar_expect_tx(sb + BAR_KV + g * 8, 16384);
            bulk_g2s(sb + g * CHUNK_BYTES, kv_src + g * 16384, 16384, sb + BAR_KV + g * 8);
        }
    }
    __syncwarp();

    {
        uint32_t c3f = 0x3F003F00u;
        asm volatile("" : "+r"(c3f));
        const uint64_t kd0 = make_desc(sb, 4096, 128, 0);
        const uint64_t vd0 = make_desc(sb + 8192, 128, 4096, 0);
#pragma unroll 1
        for (int t = 0; t < 4; t++) {
            uint32_t q[4];
            {
                const unsigned char* qp = smem + SM_Q + (wg * 4 + t) * 2048 + ((tid >> 5) & 3) * 512 + (tid & 31) * 8;
                const uint2 a = *(const uint2*)qp, b = *(const uint2*)(qp + 256);
                q[0] = a.x; q[2] = a.y; q[1] = b.x; q[3] = b.y;
            }
            float o[12];
            float s0[32], s1[32];
            uint32_t p[16];
#pragma unroll
            for (int i = 0; i < 12; i++) o[i] = 0.f;
            fence_regs<12>(o);
            {
                mbar_wait_u(sb + BAR_KV, 0);
                if (t == 0) { ts_min(5); ts_max(21); }
                wg_fence();
                qk_n64(s0, q, kd0);
                wg_commit();
                wg_wait<0>();
                fence_regs<32>(s0);
                uint64_t kd = kd0, vd = vd0;
#define HALF_STEP(SC, SN, P, KOFF, VOFF)              \
    exp_half<0>(SC, P, c3f);                         \
    wg_wait<0>();                                    \
    wg_fence();                                      \
    qk_n64(SN, q, kd + (KOFF));                      \
    pv_n24(o, P, vd + (VOFF));                       \
    pv_n24(o, P + 4, vd + (VOFF) + 16);              \
    wg_commit();                                     \
    exp_half<8>(SC + 16, P + 8, c3f);                \
    wg_fence();                                      \
    pv_n24(o, P + 8, vd + (VOFF) + 32);              \
    pv_n24(o, P + 12, vd + (VOFF) + 48);             \
    wg_commit();                                     \
    wg_wait<1>();                                    \
    fence_regs<32>(SN);
                uint32_t p2[16];
#pragma unroll 1
                for (uint32_t it = 0; it < 16; it++) {
                    mbar_wait_u(sb + BAR_KV + (((it >> 1) + 1) & 7) * 8, 0);
                    const uint64_t inc = (it & 1) ? 1152 : 128;
                    HALF_STEP(s0, s1, p, 64, 0)
                    HALF_STEP(s1, s0, p2, inc, 64)
                    kd += inc;
                    vd += inc;
                }
                wg_wait<0>();
                fence_regs<12>(o);
            }
            {
                int tid2;
                asm volatile("mov.u32 %0, %%tid.x;" : "=r"(tid2));
                const int lane = tid2 & 31;
                float n0 = bf_lo(q[0]) * bf_lo(q[0]) + bf_hi(q[0]) * bf_hi(q[0]) + bf_lo(q[2]) * bf_lo(q[2]) + bf_hi(q[2]) * bf_hi(q[2]);
                float n1 = bf_lo(q[1]) * bf_lo(q[1]) + bf_hi(q[1]) * bf_hi(q[1]) + bf_lo(q[3]) * bf_lo(q[3]) + bf_hi(q[3]) * bf_hi(q[3]);
                n0 += __shfl_xor_sync(0xffffffffu, n0, 1);
                n1 += __shfl_xor_sync(0xffffffffu, n1, 1);
                n0 += __shfl_xor_sync(0xffffffffu, n0, 2);
                n1 += __shfl_xor_sync(0xffffffffu, n1, 2);
                const float kmax2 = *(volatile float*)(smem + SM_MISC + 4);
                const bool unsafe = !(n0 * kmax2 <= 3600.f) || !(n1 * kmax2 <= 3600.f);
                uint32_t any_unsafe;
                asm volatile(
                    "{\n.reg .pred p, q;\nsetp.ne.u32 q, %1, 0;\nbar.red.or.pred p, %2, 128, q;\nselp.u32 %0, 1, 0, p;\n}"
                    : "=r"(any_unsafe) : "r"((uint32_t)unsafe), "r"(wg + 1) : "memory");
                if (lane == 0) ((volatile uint32_t*)(smem + SM_MISC + 16))[(tid2 >> 5) * 4 + t] = any_unsafe;
            }
            store_o(o, br, mb, nb, wg * 4 + t);
        }
        __syncwarp();
#pragma unroll 1
        for (int t = 0; t < 4; t++) {
            if (!__any_sync(0xffffffffu, ((volatile uint32_t*)(smem + SM_MISC + 16))[(tid >> 5) * 4 + t])) continue;
            uint32_t q[4];
            {
                const unsigned char* qp = smem + SM_Q + (wg * 4 + t) * 2048 + ((tid >> 5) & 3) * 512 + (tid & 31) * 8;
                const uint2 a = *(const uint2*)qp, b = *(const uint2*)(qp + 256);
                q[0] = a.x; q[2] = a.y; q[1] = b.x; q[3] = b.y;
            }
            float o[12], s0[32];
            uint32_t p[16];
#pragma unroll
            for (int i = 0; i < 12; i++) o[i] = 0.f;
            fence_regs<12>(o);
            attn_tile_slow(q, kd0, vd0, o, s0, p);
            store_o(o, br, mb, nb, wg * 4 + t);
        }
    }
    fence_async();
    asm volatile("bar.sync %0, 128;" ::"r"(wg + 1) : "memory");
    if ((tid & 127) == 0) signal(&g_ctr[2 + mb]);
    __syncthreads();
    ts_min(6); ts_max(22);

    const int orow0 = mb * 128 + (nb >> 2) * 64, ocol0 = (nb & 3) * 128;
    if (wg == 2) {
        if (tid == 288) {
            for (int i = 0; i < 2 * C_STAGES; i++) {
                const int kb = i >> 1, b = i & 1;
                const uint32_t s0 = sb + kb * C_STAGE_BYTES + b * 24576;
                mbar_expect_tx(sb + BAR_CF + i * 8, 24576);
                tma_2d(s0 + 8192, &maps.wo[b], ocol0, kb * 64, sb + BAR_CF + i * 8);
                tma_2d(s0 + 16384, &maps.wo[b], ocol0 + 64, kb * 64, sb + BAR_CF + i * 8);
            }
        }
        if (tid == 256) {
            spin_until(&g_ctr[2 + mb], 32);
            fence_async();
            for (int i = 0; i < 2 * C_STAGES; i++) {
                const int kb = i >> 1, b = i & 1;
                tma_2d(sb + kb * C_STAGE_BYTES + b * 24576, &maps.o, kb * 64, b * SEQ + orow0, sb + BAR_CF + i * 8);
            }
            for (int i = 0; i < 2 * C_STAGES; i++) {
                const int kb = C_STAGES + (i >> 1), b = i & 1;
                const uint32_t s0 = sb + (i >> 1) * C_STAGE_BYTES + b * 24576;
                mbar_wait(sb + BAR_CE + i * 8, 0);
                mbar_expect_tx(sb + BAR_CF + i * 8, 24576);
                tma_2d(s0, &maps.o, kb * 64, b * SEQ + orow0, sb + BAR_CF + i * 8);
                tma_2d(s0 + 8192, &maps.wo[b], ocol0, kb * 64, sb + BAR_CF + i * 8);
                tma_2d(s0 + 16384, &maps.wo[b], ocol0 + 64, kb * 64, sb + BAR_CF + i * 8);
            }
            __threadfence();
            if (atomicAdd(&g_ctr[18], 1u) == 127u) {
                for (int i = 0; i < 19; i++) g_ctr[i] = 0u;
            }
        }
    } else if (wg < 2) {
        const int warp = tid >> 5, lane = tid & 31;
        float acc[64];
#pragma unroll
        for (int i = 0; i < 64; i++) acc[i] = 0.f;
        fence_regs<64>(acc);
        const int r = lane >> 2, c = lane & 3;
        const int lrow = (warp & 3) * 16 + r;
        float g0 = 0.f, g1 = 0.f;
#pragma unroll
        for (int kb = 0; kb < 8; kb++) {
            const int st = kb % C_STAGES;
            const uint32_t s0 = sb + st * C_STAGE_BYTES + wg * 24576;
            mbar_wait_u(sb + BAR_CF + (st * 2 + wg) * 8, kb >= C_STAGES ? 1 : 0);
            if (kb == 0) {
                ts_min(8); ts_max(24);
                g0 = __ldcg(g_gate + orow0 + lrow);
                g1 = __ldcg(g_gate + orow0 + lrow + 8);
            }
            const uint64_t ad = make_desc(s0, 16, 1024, 1);
            const uint64_t bd = make_desc(s0 + 8192, 8192, 1024, 1);
            wg_fence();
#pragma unroll
            for (int kk = 0; kk < 4; kk++) mma_n128_ss(acc, ad + kk * 2, bd + kk * 128);
            wg_commit();
            if (kb >= 1 && kb <= C_STAGES) {
                wg_wait<1>();
                if (lane == 0) mbar_arrive(sb + BAR_CE + ((kb - 1) * 2 + wg) * 8);
            }
        }
        wg_wait<0>();
        fence_regs<64>(acc);
        ts_min(9); ts_max(25);
        if (wg) { g0 = bf_round(1.f - g0); g1 = bf_round(1.f - g1); }
        uint32_t t[32];
#pragma unroll
        for (int j = 0; j < 16; j++) {
            t[2 * j] = pack_bf16(g0 * bf_round(acc[4 * j]), g0 * bf_round(acc[4 * j + 1]));
            t[2 * j + 1] = pack_bf16(g1 * bf_round(acc[4 * j + 2]), g1 * bf_round(acc[4 * j + 3]));
        }
        uint32_t* xch = (uint32_t*)(smem + SM_XCH);
        const int lt = tid & 127;
#pragma unroll
        for (int j = 0; j < 16; j++) xch[(wg * 16 + j) * 128 + lt] = wg ? t[j] : t[16 + j];
        asm volatile("bar.sync 1, 256;" ::: "memory");
        unsigned char* ot = smem + wg * 16384;
#pragma unroll
        for (int j = 0; j < 16; j++) {
            const uint32_t mine = wg ? t[16 + j] : t[j];
            const uint32_t other = xch[((wg ^ 1) * 16 + j) * 128 + lt];
            const uint32_t v = pack_bf16(bf_lo(mine) + bf_lo(other), bf_hi(mine) + bf_hi(other));
            *(uint32_t*)(ot + (lrow + (j & 1) * 8) * 144 + (j >> 1) * 16 + c * 4) = v;
        }
        asm volatile("bar.sync %0, 128;" ::"r"(wg + 2) : "memory");
#pragma unroll
        for (int i = 0; i < 4; i++) {
            const int idx = i * 128 + lt, row = idx >> 3, ch = idx & 7;
            const uint4 v = *(const uint4*)(ot + row * 144 + ch * 16);
            *(uint4*)(out + (size_t)(orow0 + row) * DM + ocol0 + wg * 64 + ch * 8) = v;
        }
        ts_min(10); ts_max(26);
    }
}

typedef CUresult (*EncodeFn)(CUtensorMap*, CUtensorMapDataType, cuuint32_t, void*, const cuuint64_t*, const cuuint64_t*, const cuuint32_t*,
                             const cuuint32_t*, CUtensorMapInterleave, CUtensorMapSwizzle, CUtensorMapL2promotion, CUtensorMapFloatOOBfill);

static void encode_2d(EncodeFn fn, CUtensorMap* m, const void* ptr, uint64_t inner, uint64_t outer, uint32_t box_inner, uint32_t box_outer,
                      CUtensorMapSwizzle swz = CU_TENSOR_MAP_SWIZZLE_128B) {
    cuuint64_t dims[2] = {inner, outer};
    cuuint64_t strides[1] = {inner * 2};
    cuuint32_t box[2] = {box_inner, box_outer};
    cuuint32_t es[2] = {1, 1};
    fn(m, CU_TENSOR_MAP_DATA_TYPE_BFLOAT16, 2, (void*)ptr, dims, strides, box, es, CU_TENSOR_MAP_INTERLEAVE_NONE, swz,
       CU_TENSOR_MAP_L2_PROMOTION_L2_256B, CU_TENSOR_MAP_FLOAT_OOB_FILL_NONE);
}

extern "C" void kernel_launch(void* const* d_in, const int* in_sizes, int n_in, void* d_out, int out_size) {
    (void)in_sizes; (void)n_in; (void)out_size;
    static Maps m;
    static const void* cached[11] = {0};
    static bool attr_done = false;
    bool same = true;
    for (int i = 0; i < 11; i++) same = same && (cached[i] == d_in[i]);
    if (!same || !attr_done) {
        void* fnp = nullptr;
        cudaDriverEntryPointQueryResult qr;
        cudaGetDriverEntryPoint("cuTensorMapEncodeTiled", &fnp, cudaEnableDefault, &qr);
        EncodeFn fn = (EncodeFn)fnp;
        void* po = nullptr;
        cudaGetSymbolAddress(&po, g_O);
        encode_2d(fn, &m.x, d_in[0], DM, SEQ, 64, 128);
        encode_2d(fn, &m.wq[0], d_in[1], DM, DM, 64, 64);
        encode_2d(fn, &m.wq[1], d_in[6], DM, DM, 64, 64);
        encode_2d(fn, &m.wkv[0], d_in[2], 16, DM, 8, 256, CU_TENSOR_MAP_SWIZZLE_NONE);
        encode_2d(fn, &m.wkv[1], d_in[3], 16, DM, 8, 256, CU_TENSOR_MAP_SWIZZLE_NONE);
        encode_2d(fn, &m.wkv[2], d_in[7], 16, DM, 8, 256, CU_TENSOR_MAP_SWIZZLE_NONE);
        encode_2d(fn, &m.wkv[3], d_in[8], 16, DM, 8, 256, CU_TENSOR_MAP_SWIZZLE_NONE);
        encode_2d(fn, &m.o, po, DM, 2 * SEQ, 64, 64);
        encode_2d(fn, &m.wo[0], d_in[4], DM, DM, 64, 64);
        encode_2d(fn, &m.wo[1], d_in[9], DM, DM, 64, 64);
        cudaFuncSetAttribute(fused_kernel, cudaFuncAttributeMaxDynamicSharedMemorySize, SMEM_TOTAL);
        for (int i = 0; i < 11; i++) cached[i] = d_in[i];
        attr_done = true;
    }
    cudaLaunchAttribute at[1];
    at[0].id = cudaLaunchAttributeCooperative;
    at[0].val.cooperative = 1;
    cudaLaunchConfig_t cfg = {};
    cfg.stream = cudaStreamPerThread;
    cfg.attrs = at;
    cfg.numAttrs = 1;
    cfg.gridDim = dim3(128);
    cfg.blockDim = dim3(512);
    cfg.dynamicSmemBytes = SMEM_TOTAL;
    cudaLaunchKernelEx(&cfg, fused_kernel, m, (const bf16*)d_in[0], (const bf16*)d_in[10], (const bf16*)d_in[1], (const bf16*)d_in[6],
                       (const bf16*)d_in[4], (const bf16*)d_in[9], (bf16*)d_out);
}
```

```cpp
#include <cuda_runtime.h>
#include <cuda_bf16.h>
#include <cuda.h>
#include <stdint.h>

typedef __nv_bfloat16 bf16;

#define SEQ 2048
#define DM 512
#define ROWS 65536

__device__ __align__(1024) bf16 g_KV[2 * 4 * SEQ * 8];
__device__ __align__(1024) bf16 g_O[2 * ROWS * 16];
__device__ float g_gate[SEQ];
__device__ __align__(16) float g_nrm[512];
__device__ unsigned int g_ctr[72];

#define ts_min(i)
#define ts_max(i)
__device__ __forceinline__ uint32_t smem_u32(const void* p) { return (uint32_t)__cvta_generic_to_shared(p); }
__device__ __forceinline__ uint64_t make_desc(uint32_t saddr, uint32_t lbo, uint32_t sbo, uint32_t swz) {
    uint64_t d = 0;
    d |= (uint64_t)((saddr & 0x3FFFF) >> 4);
    d |= (uint64_t)((lbo & 0x3FFFF) >> 4) << 16;
    d |= (uint64_t)((sbo & 0x3FFFF) >> 4) << 32;
    d |= (uint64_t)swz << 62;
    return d;
}
__device__ __forceinline__ void wg_fence() { asm volatile("wgmma.fence.sync.aligned;" ::: "memory"); }
__device__ __forceinline__ void wg_commit() { asm volatile("wgmma.commit_group.sync.aligned;" ::: "memory"); }
template <int N> __device__ __forceinline__ void wg_wait() { asm volatile("wgmma.wait_group.sync.aligned %0;" ::"n"(N) : "memory"); }
template <int N> __device__ __forceinline__ void fence_regs(float* d) {
#pragma unroll
    for (int i = 0; i < N; i++) asm volatile("" : "+f"(d[i])::"memory");
}
__device__ __forceinline__ void mbar_init(uint32_t bar, uint32_t cnt) { asm volatile("mbarrier.init.shared::cta.b64 [%0], %1;" ::"r"(bar), "r"(cnt)); }
__device__ __forceinline__ void mbar_expect_tx(uint32_t bar, uint32_t bytes) {
    asm volatile("mbarrier.arrive.expect_tx.shared::cta.b64 _, [%0], %1;" ::"r"(bar), "r"(bytes) : "memory");
}
__device__ __forceinline__ void mbar_arrive(uint32_t bar) { asm volatile("mbarrier.arrive.shared::cta.b64 _, [%0];" ::"r"(bar) : "memory"); }
__device__ __forceinline__ void mbar_wait(uint32_t bar, uint32_t parity) {
    asm volatile(
        "{\n.reg .pred p;\n"
        "WAIT_LOOP:\n"
        "mbarrier.try_wait.parity.shared::cta.b64 p, [%0], %1;\n"
        "@p bra DONE;\n"
        "bra WAIT_LOOP;\n"
        "DONE:\n}" ::"r"(bar), "r"(parity) : "memory");
}
__device__ __forceinline__ void mbar_wait_u(uint32_t bar, uint32_t parity) {
    uint32_t ok;
    do {
        asm volatile(
            "{\n.reg .pred p;\nmbarrier.try_wait.parity.shared::cta.b64 p, [%1], %2;\nselp.u32 %0, 1, 0, p;\n}"
            : "=r"(ok) : "r"(bar), "r"(parity) : "memory");
    } while (!__all_sync(0xffffffffu, ok));
}
__device__ __forceinline__ void bulk_g2s(uint32_t dst, const void* src, uint32_t bytes, uint32_t bar) {
    asm volatile("cp.async.bulk.shared::cluster.global.mbarrier::complete_tx::bytes [%0], [%1], %2, [%3];" ::"r"(dst), "l"(src), "r"(bytes), "r"(bar) : "memory");
}
__device__ __forceinline__ void tma_2d(uint32_t dst, const CUtensorMap* map, int c0, int c1, uint32_t bar) {
    asm volatile("cp.async.bulk.tensor.2d.shared::cluster.global.mbarrier::complete_tx::bytes [%0], [%1, {%3, %4}], [%2];" ::"r"(dst), "l"(map), "r"(bar), "r"(c0), "r"(c1) : "memory");
}
__device__ __forceinline__ void l2_prefetch(const void* p, uint32_t bytes) {
    asm volatile("cp.async.bulk.prefetch.L2.global [%0], %1;" ::"l"(p), "r"(bytes) : "memory");
}
__device__ __forceinline__ void pdl_launch() { asm volatile("griddepcontrol.launch_dependents;" ::: "memory"); }
__device__ __forceinline__ void pdl_wait() { asm volatile("griddepcontrol.wait;" ::: "memory"); }
__device__ __forceinline__ void fence_async() { asm volatile("fence.proxy.async;" ::: "memory"); }
__device__ __forceinline__ uint32_t pack_bf16(float lo, float hi) {
    uint32_t r;
    asm("cvt.rn.bf16x2.f32 %0, %1, %2;" : "=r"(r) : "f"(hi), "f"(lo));
    return r;
}
__device__ __forceinline__ float bf_lo(uint32_t u) { return __uint_as_float(u << 16); }
__device__ __forceinline__ float bf_hi(uint32_t u) { return __uint_as_float(u & 0xFFFF0000u); }
__device__ __forceinline__ float bf_round(float x) { return __bfloat162float(__float2bfloat16_rn(x)); }

#define A8(b) "+f"(d[b + 0]), "+f"(d[b + 1]), "+f"(d[b + 2]), "+f"(d[b + 3]), "+f"(d[b + 4]), "+f"(d[b + 5]), "+f"(d[b + 6]), "+f"(d[b + 7])
#define W8(b) "=f"(d[b + 0]), "=f"(d[b + 1]), "=f"(d[b + 2]), "=f"(d[b + 3]), "=f"(d[b + 4]), "=f"(d[b + 5]), "=f"(d[b + 6]), "=f"(d[b + 7])

__device__ __forceinline__ void mma_n8_ss(float* d, uint64_t ad, uint64_t bd) {
    asm volatile("wgmma.mma_async.sync.aligned.m64n8k16.f32.bf16.bf16 {%0,%1,%2,%3}, %4, %5, 1, 1, 1, 0, 1;"
                 : "+f"(d[0]), "+f"(d[1]), "+f"(d[2]), "+f"(d[3])
                 : "l"(ad), "l"(bd));
}
__device__ __forceinline__ void mma_n128_ss(float* d, uint64_t ad, uint64_t bd) {
    asm volatile(
        "wgmma.mma_async.sync.aligned.m64n128k16.f32.bf16.bf16 "
        "{%0,%1,%2,%3,%4,%5,%6,%7,%8,%9,%10,%11,%12,%13,%14,%15,%16,%17,%18,%19,%20,%21,%22,%23,%24,%25,%26,%27,%28,%29,%30,%31,"
        "%32,%33,%34,%35,%36,%37,%38,%39,%40,%41,%42,%43,%44,%45,%46,%47,%48,%49,%50,%51,%52,%53,%54,%55,%56,%57,%58,%59,%60,%61,%62,%63}, "
        "%64, %65, 1, 1, 1, 0, 1;"
        : A8(0), A8(8), A8(16), A8(24), A8(32), A8(40), A8(48), A8(56)
        : "l"(ad), "l"(bd));
}
__device__ __forceinline__ void qk_n64(float* d, const uint32_t* a, uint64_t bd) {
    asm volatile(
        "wgmma.mma_async.sync.aligned.m64n64k16.f32.bf16.bf16 "
        "{%0,%1,%2,%3,%4,%5,%6,%7,%8,%9,%10,%11,%12,%13,%14,%15,%16,%17,%18,%19,%20,%21,%22,%23,%24,%25,%26,%27,%28,%29,%30,%31}, "
        "{%32,%33,%34,%35}, %36, 0, 1, 1, 0;"
        : W8(0), W8(8), W8(16), W8(24)
        : "r"(a[0]), "r"(a[1]), "r"(a[2]), "r"(a[3]), "l"(bd));
}
__device__ __forceinline__ void pv_n24(float* d, const uint32_t* a, uint64_t bd) {
    asm volatile(
        "wgmma.mma_async.sync.aligned.m64n24k16.f32.bf16.bf16 {%0,%1,%2,%3,%4,%5,%6,%7,%8,%9,%10,%11}, {%12,%13,%14,%15}, %16, 1, 1, 1, 1;"
        : A8(0), "+f"(d[8]), "+f"(d[9]), "+f"(d[10]), "+f"(d[11])
        : "r"(a[0]), "r"(a[1]), "r"(a[2]), "r"(a[3]), "l"(bd));
}

__device__ __forceinline__ float ex2(float x) {
    float e;
    asm("ex2.approx.ftz.f32 %0, %1;" : "=f"(e) : "f"(x));
    return e;
}
__device__ __forceinline__ uint32_t exp_pair_mufu(float x0, float x1) { return pack_bf16(ex2(x0), ex2(x1)); }

#define MAGIC0 (98304.0f + 127.0f - 75.0f / 128.0f)
#define MAGIC1 (98304.0f + 127.0f - 75.0f / 128.0f - 143.5f)
template <int PRM>
__device__ __forceinline__ uint32_t exp_pair_poly(float x0, float x1, uint32_t c3f) {
    float t0 = x0 + MAGIC0;
    float t1 = x1 + (PRM ? MAGIC0 : MAGIC1);
    uint32_t L, y2, E, r;
    if (PRM)
        asm("prmt.b32 %0, %1, %2, 0x5410;" : "=r"(L) : "r"(__float_as_uint(t0)), "r"(__float_as_uint(t1)));
    else
        L = __float_as_uint(t1) * 65536u + __float_as_uint(t0);
    asm("lop3.b32 %0, %1, 0x007F007F, %2, 0xEA;" : "=r"(y2) : "r"(L), "r"(c3f));
    E = L & 0x7F807F80u;
    asm("fma.rn.bf16x2 %0, %1, %2, %3;" : "=r"(r) : "r"(L), "r"(y2), "r"(E));
    return r;
}
#define EXP_MASK 0x5454u
template <int BASE>
__device__ __forceinline__ void exp_half(const float* s, uint32_t* p, uint32_t c3f) {
#pragma unroll
    for (int i = 0; i < 8; i++) {
        if ((EXP_MASK >> (BASE + i)) & 1) p[i] = exp_pair_mufu(s[2 * i], s[2 * i + 1]);
        else p[i] = exp_pair_poly<0>(s[2 * i], s[2 * i + 1], c3f);
    }
}

struct Maps {
    CUtensorMap x;
    CUtensorMap wq[2];
    CUtensorMap wkv[4];
    CUtensorMap o;
    CUtensorMap wo[2];
};
#define SM_X 20480
#define SM_WKV 151552
#define SM_WQ 159744
#define CHUNK_BYTES 20480
#define SM_Q 163840
#define C_STAGES 4
#define C_STAGE_BYTES 49152
#define SM_XCH 196608
#define SM_BAR 225280
#define BAR_X (SM_BAR)
#define BAR_KV (SM_BAR + 64)
#define BAR_CF (SM_BAR + 128)
#define BAR_CE (SM_BAR + 192)
#define BAR_WF (SM_BAR + 256)
#define BAR_WE (SM_BAR + 288)
#define BAR_WKV (SM_BAR + 320)
#define SM_MISC (SM_BAR + 384)
#define SMEM_TOTAL (SM_BAR + 1024 + 1024)

__device__ __forceinline__ void spin_until(const unsigned int* ctr, unsigned int target) {
    unsigned int v;
    for (unsigned int it = 0; it < (1u << 26); it++) {
        asm volatile("ld.acquire.gpu.global.u32 %0, [%1];" : "=r"(v) : "l"(ctr) : "memory");
        if (v >= target) return;
    }
    __trap();
}
__device__ __forceinline__ void signal(unsigned int* ctr) {
    asm volatile("red.release.gpu.global.add.u32 [%0], 1;" ::"l"(ctr) : "memory");
}

__device__ __forceinline__ void attn_tile_slow(const uint32_t* qq, uint64_t kd0, uint64_t vd0, float* o, float* s, uint32_t* p) {
    float m0 = -INFINITY, m1 = -INFINITY;
#pragma unroll 1
    for (int ch = 0; ch < 32; ch++) {
        wg_fence();
        qk_n64(s, qq, kd0 + (uint64_t)((ch >> 2) * 1280 + (ch & 3) * 64));
        wg_commit();
        wg_wait<0>();
        fence_regs<32>(s);
#pragma unroll
        for (int j = 0; j < 8; j++) {
            m0 = fmaxf(m0, fmaxf(s[4 * j], s[4 * j + 1]));
            m1 = fmaxf(m1, fmaxf(s[4 * j + 2], s[4 * j + 3]));
        }
    }
    m0 = fmaxf(m0, __shfl_xor_sync(0xffffffffu, m0, 1));
    m1 = fmaxf(m1, __shfl_xor_sync(0xffffffffu, m1, 1));
    m0 = fmaxf(m0, __shfl_xor_sync(0xffffffffu, m0, 2));
    m1 = fmaxf(m1, __shfl_xor_sync(0xffffffffu, m1, 2));
#pragma unroll 1
    for (int ch = 0; ch < 32; ch++) {
        wg_fence();
        qk_n64(s, qq, kd0 + (uint64_t)((ch >> 2) * 1280 + (ch & 3) * 64));
        wg_commit();
        wg_wait<0>();
        fence_regs<32>(s);
#pragma unroll
        for (int j = 0; j < 8; j++) {
            p[2 * j] = exp_pair_mufu(s[4 * j] - m0, s[4 * j + 1] - m0);
            p[2 * j + 1] = exp_pair_mufu(s[4 * j + 2] - m1, s[4 * j + 3] - m1);
        }
        wg_fence();
#pragma unroll
        for (int j = 0; j < 4; j++) pv_n24(o, p + 4 * j, vd0 + (uint64_t)((ch >> 2) * 1280 + (ch & 3) * 64 + 16 * j));
        wg_commit();
        wg_wait<0>();
        fence_regs<12>(o);
    }
}

#define TILE_OF(w, t) (((((t) >> 1) * 4 + (w)) << 1) + ((t) & 1))
__device__ __forceinline__ void store_o(const float* o, int br, int mb, int nb, int tile) {
    int tid2;
    asm volatile("mov.u32 %0, %%tid.x;" : "=r"(tid2));
    const int lane = tid2 & 31;
    const float l0 = __shfl_sync(0xffffffffu, o[8], lane & ~3);
    const float l1 = __shfl_sync(0xffffffffu, o[10], lane & ~3);
    const float i0 = 1.f / l0, i1 = 1.f / l1;
    const uint32_t row = (uint32_t)(br * SEQ + mb * 128 + (tile & 1) * 64 + ((tid2 >> 5) & 3) * 16 + (lane >> 2));
    bf16* op = g_O + row * DM + ((nb & 3) * 8 + (tile >> 1)) * 16 + (lane & 3) * 2;
    *(uint32_t*)(op) = pack_bf16(o[0] * i0, o[1] * i0);
    *(uint32_t*)(op + 8 * DM) = pack_bf16(o[2] * i1, o[3] * i1);
    *(uint32_t*)(op + 8) = pack_bf16(o[4] * i0, o[5] * i0);
    *(uint32_t*)(op + 8 * DM + 8) = pack_bf16(o[6] * i1, o[7] * i1);
}

__global__ void __launch_bounds__(512, 1) fused_kernel(const __grid_constant__ Maps maps, const bf16* __restrict__ x, const bf16* __restrict__ gate_w,
                                                        const bf16* __restrict__ wqa, const bf16* __restrict__ wqb, const bf16* __restrict__ woa,
                                                        const bf16* __restrict__ wob, bf16* __restrict__ out) {
    extern __shared__ unsigned char smem_raw[];
    const uint32_t sb = (smem_u32(smem_raw) + 1023) & ~1023u;
    unsigned char* smem = smem_raw + (sb - smem_u32(smem_raw));
    const int tid = threadIdx.x;
    const int wg = __shfl_sync(0xffffffffu, tid >> 7, 0);
    const int mb = blockIdx.x >> 3, nb = blockIdx.x & 7;
    const int br = nb >> 2;
    ts_min(0); ts_max(16);
    if (tid == 384) {
        for (int i = 0; i < 8; i++) mbar_init(sb + BAR_X + i * 8, 1);
        mbar_init(sb + BAR_WKV, 1);
        asm volatile("fence.mbarrier_init.release.cluster;" ::: "memory");
        mbar_expect_tx(sb + BAR_WKV, 8192);
        tma_2d(sb + SM_WKV, &maps.wkv[nb >> 1], (nb & 1) * 8, 0, sb + BAR_WKV);
        tma_2d(sb + SM_WKV + 4096, &maps.wkv[nb >> 1], (nb & 1) * 8, 256, sb + BAR_WKV);
        for (int kb = 0; kb < 8; kb++) {
            mbar_expect_tx(sb + BAR_X + kb * 8, 16384);
            tma_2d(sb + SM_X + kb * 16384, &maps.x, kb * 64, mb * 128, sb + BAR_X + kb * 8);
        }
    }
    if (tid == 352) asm volatile("prefetch.tensormap [%0];" ::"l"(&maps.x) : "memory");
    if (tid == 0) {
        for (int i = 0; i < 8; i++) {
            mbar_init(sb + BAR_KV + i * 8, 1);
            mbar_init(sb + BAR_CF + i * 8, 1);
            mbar_init(sb + BAR_CE + i * 8, 4);
        }
        for (int i = 0; i < 4; i++) {
            mbar_init(sb + BAR_WF + i * 8, 1);
            mbar_init(sb + BAR_WE + i * 8, 8);
        }
        asm volatile("fence.mbarrier_init.release.cluster;" ::: "memory");
    }
    if (tid == 416) {
        l2_prefetch(wqa + (size_t)blockIdx.x * 2048, 4096);
        l2_prefetch(wqb + (size_t)blockIdx.x * 2048, 4096);
        asm volatile("prefetch.tensormap [%0];" ::"l"(&maps.wq[br]) : "memory");
        asm volatile("prefetch.tensormap [%0];" ::"l"(&maps.o) : "memory");
        asm volatile("prefetch.tensormap [%0];" ::"l"(&maps.wo[0]) : "memory");
        asm volatile("prefetch.tensormap [%0];" ::"l"(&maps.wo[1]) : "memory");
    }
    __syncthreads();

    const unsigned char* kv_src = (const unsigned char*)g_KV + (size_t)br * 131072;
    if (wg < 2) {
        const int warp = tid >> 5, lane = tid & 31;
        float acc[64];
#pragma unroll
        for (int i = 0; i < 64; i++) acc[i] = 0.f;
        fence_regs<64>(acc);
        asm volatile("bar.sync 3, 384;" ::: "memory");
#pragma unroll
        for (int kb = 0; kb < 8; kb++) {
            const int st = kb & 3;
            mbar_wait_u(sb + BAR_WF + st * 8, kb >> 2);
            if (kb == 0) { ts_min(12); ts_max(28); }
            const uint64_t ad = make_desc(sb + SM_X + kb * 16384 + wg * 8192, 16, 1024, 1);
            const uint64_t bd = make_desc(sb + SM_WQ + st * 16384, 8192, 1024, 1);
            wg_fence();
#pragma unroll
            for (int kk = 0; kk < 4; kk++) mma_n128_ss(acc, ad + kk * 2, bd + kk * 128);
            wg_commit();
            if (kb >= 1 && kb <= 4) {
                wg_wait<1>();
                if (lane == 0) mbar_arrive(sb + BAR_WE + (kb - 1) * 8);
            }
        }
        wg_wait<0>();
        fence_regs<64>(acc);
        ts_min(1); ts_max(17);
        asm volatile("bar.sync 1, 384;" ::: "memory");
        const int r = lane >> 2, c = lane & 3;
        const float qs = 0.25f * 1.4426950408889634f;
        unsigned char* qp = smem + SM_Q + wg * 2048 + ((warp & 3) * 16 + r) * 32 + c * 8;
#pragma unroll
        for (int h = 0; h < 8; h++) {
            const float* a = acc + h * 8;
            *(uint2*)(qp + h * 4096) = make_uint2(pack_bf16(a[0] * qs, a[1] * qs), pack_bf16(a[4] * qs, a[5] * qs));
            *(uint2*)(qp + h * 4096 + 256) = make_uint2(pack_bf16(a[2] * qs, a[3] * qs), pack_bf16(a[6] * qs, a[7] * qs));
        }
        ts_min(2); ts_max(18);
    } else if (wg == 2) {
        const int warp = (tid >> 5) & 3, lane = tid & 31;
        float a0[4] = {0.f, 0.f, 0.f, 0.f}, a1[4] = {0.f, 0.f, 0.f, 0.f};
        fence_regs<4>(a0);
        fence_regs<4>(a1);
        *(uint4*)(smem + 16384 + (tid & 127) * 16) = make_uint4(0x00003F80u, 0, 0, 0);
        *(uint4*)(smem + 18432 + (tid & 127) * 16) = make_uint4(0x00003F80u, 0, 0, 0);
        mbar_wait_u(sb + BAR_WKV, 0);
#pragma unroll
        for (int kb = 0; kb < 8; kb++) {
            mbar_wait_u(sb + BAR_X + kb * 8, 0);
            const uint64_t ad = make_desc(sb + SM_X + kb * 16384, 16, 1024, 1);
            const uint64_t bd = make_desc(sb + SM_WKV + kb * 1024, 128, 128, 0);
            wg_fence();
#pragma unroll
            for (int kk = 0; kk < 4; kk++) {
                mma_n8_ss(a0, ad + kk * 2, bd + kk * 16);
                mma_n8_ss(a1, ad + 512 + kk * 2, bd + kk * 16);
            }
            wg_commit();
        }
        wg_wait<0>();
        fence_regs<4>(a0);
        fence_regs<4>(a1);
        asm volatile("bar.arrive 3, 384;" ::: "memory");
        ts_min(14); ts_max(30);
        const int r = lane >> 2, c = lane & 3;
        const int row = mb * 128 + warp * 16 + r;
        const uint32_t k0 = pack_bf16(a0[0], a0[1]), k1 = pack_bf16(a0[2], a0[3]);
        const uint32_t k2 = pack_bf16(a1[0], a1[1]), k3 = pack_bf16(a1[2], a1[3]);
        bf16* kvp = g_KV + (size_t)br * 65536 + (row >> 8) * 8192 + (nb & 3) * 2048 + (row & 255) * 8 + 2 * c;
        *(uint32_t*)kvp = k0;
        *(uint32_t*)(kvp + 64) = k1;
        *(uint32_t*)(kvp + 512) = k2;
        *(uint32_t*)(kvp + 576) = k3;
        unsigned int mu;
        if (((nb >> 1) & 1) == 0) {
            float n0 = bf_lo(k0) * bf_lo(k0) + bf_hi(k0) * bf_hi(k0);
            float n1 = bf_lo(k1) * bf_lo(k1) + bf_hi(k1) * bf_hi(k1);
            float n2 = bf_lo(k2) * bf_lo(k2) + bf_hi(k2) * bf_hi(k2);
            float n3 = bf_lo(k3) * bf_lo(k3) + bf_hi(k3) * bf_hi(k3);
#pragma unroll
            for (int sft = 1; sft <= 2; sft <<= 1) {
                n0 += __shfl_xor_sync(0xffffffffu, n0, sft);
                n1 += __shfl_xor_sync(0xffffffffu, n1, sft);
                n2 += __shfl_xor_sync(0xffffffffu, n2, sft);
                n3 += __shfl_xor_sync(0xffffffffu, n3, sft);
            }
            mu = max(max(__float_as_uint(n0), __float_as_uint(n1)), max(__float_as_uint(n2), __float_as_uint(n3)));
        } else {
            mu = max(max(max((k0 << 16) & 0x7FFFFFFFu, k0 & 0x7FFF0000u), max((k1 << 16) & 0x7FFFFFFFu, k1 & 0x7FFF0000u)),
                     max(max((k2 << 16) & 0x7FFFFFFFu, k2 & 0x7FFF0000u), max((k3 << 16) & 0x7FFFFFFFu, k3 & 0x7FFF0000u)));
        }
        mu = __reduce_max_sync(0xffffffffu, mu);
        asm volatile("fence.proxy.async.global;" ::: "memory");
        __syncwarp();
        if (lane == 0) {
            g_nrm[(nb * 16 + mb) * 4 + warp] = __uint_as_float(mu);
            signal(&g_ctr[br]);
            ts_min(13); ts_max(29);
        }
        asm volatile("bar.sync 1, 384;" ::: "memory");
#pragma unroll
        for (int i = 1; i < 8; i++) {
            *(uint4*)(smem + i * CHUNK_BYTES + 16384 + (tid & 127) * 16) = make_uint4(0x00003F80u, 0, 0, 0);
            *(uint4*)(smem + i * CHUNK_BYTES + 18432 + (tid & 127) * 16) = make_uint4(0x00003F80u, 0, 0, 0);
        }
        asm volatile("fence.proxy.async.shared::cta;" ::: "memory");
    } else {
        const int lane = tid & 31, w = (tid >> 5) & 3;
        if (w == 0) {
            if (lane == 0) {
                mbar_wait(sb + BAR_X + 56, 0);
                ts_min(11); ts_max(27);
                for (int st = 0; st < 4; st++) {
                    mbar_expect_tx(sb + BAR_WF + st * 8, 16384);
                    tma_2d(sb + SM_WQ + st * 16384, &maps.wq[br], (nb & 3) * 128, st * 64, sb + BAR_WF + st * 8);
                    tma_2d(sb + SM_WQ + st * 16384 + 8192, &maps.wq[br], (nb & 3) * 128 + 64, st * 64, sb + BAR_WF + st * 8);
                }
                for (int st = 0; st < 4; st++) {
                    mbar_wait(sb + BAR_WE + st * 8, 0);
                    mbar_expect_tx(sb + BAR_WF + st * 8, 16384);
                    tma_2d(sb + SM_WQ + st * 16384, &maps.wq[br], (nb & 3) * 128, (st + 4) * 64, sb + BAR_WF + st * 8);
                    tma_2d(sb + SM_WQ + st * 16384 + 8192, &maps.wq[br], (nb & 3) * 128 + 64, (st + 4) * 64, sb + BAR_WF + st * 8);
                }
                l2_prefetch(woa + (size_t)blockIdx.x * 2048, 4096);
                l2_prefetch(wob + (size_t)blockIdx.x * 2048, 4096);
                spin_until(&g_ctr[br], 256);
                fence_async();
                ts_min(4); ts_max(20);
                mbar_expect_tx(sb + BAR_KV, 16384);
                bulk_g2s(sb, kv_src, 16384, sb + BAR_KV);
            }
            __syncwarp();
            const uint4 hk = __ldcg((const uint4*)g_nrm + br * 64 + lane);
            const uint4 hv = __ldcg((const uint4*)g_nrm + br * 64 + 32 + lane);
            unsigned int h = max(max(hk.x, hk.y), max(hk.z, hk.w));
            const unsigned int nv = max(max(hv.x, hv.y), max(hv.z, hv.w));
#pragma unroll
            for (int sft = 8; sft > 0; sft >>= 1) h = max(h, __shfl_xor_sync(0xffffffffu, h, sft));
            float kmax2 = __uint_as_float(h) + __uint_as_float(__shfl_xor_sync(0xffffffffu, h, 16));
            const float vmax = __uint_as_float(__reduce_max_sync(0xffffffffu, nv));
            if (!(vmax <= 1.0e15f)) kmax2 = __uint_as_float(0x7FC00000u);
            if (lane == 0) *(volatile float*)(smem + SM_MISC + 4) = kmax2;
        } else {
            const uint4* gw = (const uint4*)(gate_w + lane * 16);
            const uint4 w0 = __ldg(gw), w1 = __ldg(gw + 1);
            const uint32_t wv[8] = {w0.x, w0.y, w0.z, w0.w, w1.x, w1.y, w1.z, w1.w};
            uint4 xa[6][2];
#pragma unroll
            for (int rr = 0; rr < 6; rr++) {
                const int lr = min(w - 1 + rr * 3, 15);
                const uint4* xp = (const uint4*)(x + (size_t)(blockIdx.x * 16 + lr) * DM + lane * 16);
                xa[rr][0] = __ldg(xp);
                xa[rr][1] = __ldg(xp + 1);
            }
#pragma unroll
            for (int rr = 0; rr < 6; rr++) {
                const uint32_t xv[8] = {xa[rr][0].x, xa[rr][0].y, xa[rr][0].z, xa[rr][0].w, xa[rr][1].x, xa[rr][1].y, xa[rr][1].z, xa[rr][1].w};
                float sum = 0.f;
#pragma unroll
                for (int i = 0; i < 8; i++) {
                    sum += bf_round(bf_lo(xv[i]) * bf_lo(wv[i]));
                    sum += bf_round(bf_hi(xv[i]) * bf_hi(wv[i]));
                }
#pragma unroll
                for (int o = 16; o > 0; o >>= 1) sum += __shfl_xor_sync(0xffffffffu, sum, o);
                if (lane == 0) {
                    sum = bf_round(sum);
                    g_gate[blockIdx.x * 16 + min(w - 1 + rr * 3, 15)] = bf_round(1.f / (1.f + __expf(-sum)));
                }
            }
        }
    }
    __syncthreads();
    if (tid == 384) {
        for (int g = 1; g < 8; g++) {
            mbar_expect_tx(sb + BAR_KV + g * 8, 16384);
            bulk_g2s(sb + g * CHUNK_BYTES, kv_src + g * 16384, 16384, sb + BAR_KV + g * 8);
        }
    }
    __syncwarp();

    {
        uint32_t c3f = 0x3F003F00u;
        asm volatile("" : "+r"(c3f));
        const uint64_t kd0 = make_desc(sb, 4096, 128, 0);
        const uint64_t vd0 = make_desc(sb + 8192, 128, 4096, 0);
#pragma unroll 1
        for (int t = 0; t < 4; t++) {
            uint32_t q[4];
            {
                const unsigned char* qp = smem + SM_Q + TILE_OF(wg, t) * 2048 + ((tid >> 5) & 3) * 512 + (tid & 31) * 8;
                const uint2 a = *(const uint2*)qp, b = *(const uint2*)(qp + 256);
                q[0] = a.x; q[2] = a.y; q[1] = b.x; q[3] = b.y;
            }
            float o[12];
            float s0[32], s1[32];
            uint32_t p[16];
#pragma unroll
            for (int i = 0; i < 12; i++) o[i] = 0.f;
            fence_regs<12>(o);
            {
                mbar_wait_u(sb + BAR_KV, 0);
                if (t == 0) { ts_min(5); ts_max(21); }
                wg_fence();
                qk_n64(s0, q, kd0);
                wg_commit();
                wg_wait<0>();
                fence_regs<32>(s0);
                uint64_t kd = kd0, vd = vd0;
#define HALF_STEP(SC, SN, P, KOFF, VOFF)              \
    exp_half<0>(SC, P, c3f);                         \
    wg_wait<0>();                                    \
    wg_fence();                                      \
    qk_n64(SN, q, kd + (KOFF));                      \
    pv_n24(o, P, vd + (VOFF));                       \
    pv_n24(o, P + 4, vd + (VOFF) + 16);              \
    wg_commit();                                     \
    exp_half<8>(SC + 16, P + 8, c3f);                \
    wg_fence();                                      \
    pv_n24(o, P + 8, vd + (VOFF) + 32);              \
    pv_n24(o, P + 12, vd + (VOFF) + 48);             \
    wg_commit();                                     \
    wg_wait<1>();                                    \
    fence_regs<32>(SN);
                uint32_t p2[16];
                uint32_t kvbar = sb + BAR_KV + 8;
#pragma unroll 1
                for (uint32_t g = 0; g < 8; g++) {
                    if (t == 0 && g < 7) mbar_wait_u(kvbar, 0);
                    kvbar += 8;
                    if (g == 2 && t > 0) {
                        if ((tid & 127) == 96 && ((volatile uint32_t*)(smem + SM_MISC + 16))[(tid >> 5) * 4 + t - 1] == 0u)
                            signal(&g_ctr[2 + mb * 4 + t - 1]);
                        __syncwarp();
                    }
                    HALF_STEP(s0, s1, p, 64, 0)
                    HALF_STEP(s1, s0, p2, 128, 64)
                    HALF_STEP(s0, s1, p, 192, 128)
                    HALF_STEP(s1, s0, p2, 1280, 192)
                    kd += 1280;
                    vd += 1280;
                }
                wg_wait<0>();
                fence_regs<12>(o);
            }
            {
                int tid2;
                asm volatile("mov.u32 %0, %%tid.x;" : "=r"(tid2));
                const int lane = tid2 & 31;
                float n0 = bf_lo(q[0]) * bf_lo(q[0]) + bf_hi(q[0]) * bf_hi(q[0]) + bf_lo(q[2]) * bf_lo(q[2]) + bf_hi(q[2]) * bf_hi(q[2]);
                float n1 = bf_lo(q[1]) * bf_lo(q[1]) + bf_hi(q[1]) * bf_hi(q[1]) + bf_lo(q[3]) * bf_lo(q[3]) + bf_hi(q[3]) * bf_hi(q[3]);
                n0 += __shfl_xor_sync(0xffffffffu, n0, 1);
                n1 += __shfl_xor_sync(0xffffffffu, n1, 1);
                n0 += __shfl_xor_sync(0xffffffffu, n0, 2);
                n1 += __shfl_xor_sync(0xffffffffu, n1, 2);
                const float kmax2 = *(volatile float*)(smem + SM_MISC + 4);
                const bool unsafe = !(n0 * kmax2 <= 3600.f) || !(n1 * kmax2 <= 3600.f);
                uint32_t any_unsafe;
                asm volatile(
                    "{\n.reg .pred p, q;\nsetp.ne.u32 q, %1, 0;\nbar.red.or.pred p, %2, 128, q;\nselp.u32 %0, 1, 0, p;\n}"
                    : "=r"(any_unsafe) : "r"((uint32_t)unsafe), "r"(wg + 1) : "memory");
                if (lane == 0) ((volatile uint32_t*)(smem + SM_MISC + 16))[(tid2 >> 5) * 4 + t] = any_unsafe;
            }
            store_o(o, br, mb, nb, TILE_OF(wg, t));
            asm volatile("fence.proxy.async.global;" ::: "memory");
            asm volatile("bar.sync %0, 128;" ::"r"(wg + 1) : "memory");
        }
        __syncwarp();
#pragma unroll 1
        for (int t = 0; t < 4; t++) {
            if (!__any_sync(0xffffffffu, ((volatile uint32_t*)(smem + SM_MISC + 16))[(tid >> 5) * 4 + t])) continue;
            uint32_t q[4];
            {
                const unsigned char* qp = smem + SM_Q + TILE_OF(wg, t) * 2048 + ((tid >> 5) & 3) * 512 + (tid & 31) * 8;
                const uint2 a = *(const uint2*)qp, b = *(const uint2*)(qp + 256);
                q[0] = a.x; q[2] = a.y; q[1] = b.x; q[3] = b.y;
            }
            float o[12], s0[32];
            uint32_t p[16];
#pragma unroll
            for (int i = 0; i < 12; i++) o[i] = 0.f;
            fence_regs<12>(o);
            attn_tile_slow(q, kd0, vd0, o, s0, p);
            store_o(o, br, mb, nb, TILE_OF(wg, t));
        }
    }
    fence_async();
    asm volatile("bar.sync %0, 128;" ::"r"(wg + 1) : "memory");
    if (((tid >> 5) & 3) == 3) {
        asm volatile("bar.arrive 0, 512;" ::: "memory");
        if ((tid & 31) == 0) {
            for (int t = 0; t < 4; t++)
                if (t == 3 || ((volatile uint32_t*)(smem + SM_MISC + 16))[(tid >> 5) * 4 + t] != 0u) signal(&g_ctr[2 + mb * 4 + t]);
        }
        __syncwarp();
    } else {
        asm volatile("bar.sync 0, 512;" ::: "memory");
    }
    ts_min(6); ts_max(22);

    const int orow0 = mb * 128 + (nb >> 2) * 64, ocol0 = (nb & 3) * 128;
    if (wg == 2) {
        if (tid == 288) {
            for (int i = 0; i < 2 * C_STAGES; i++) {
                const int st = i >> 1, b = i & 1;
                const uint32_t s0 = sb + st * C_STAGE_BYTES + b * 24576;
                mbar_expect_tx(sb + BAR_CF + i * 8, 24576);
                tma_2d(s0 + 8192, &maps.wo[b], ocol0, st * 128, sb + BAR_CF + i * 8);
                tma_2d(s0 + 16384, &maps.wo[b], ocol0 + 64, st * 128, sb + BAR_CF + i * 8);
            }
        }
        if (tid == 256) {
            spin_until(&g_ctr[2 + mb * 4 + (nb >> 2)], 32);
            fence_async();
            for (int i = 0; i < 2 * C_STAGES; i++) {
                const int st = i >> 1, b = i & 1;
                tma_2d(sb + st * C_STAGE_BYTES + b * 24576, &maps.o, st * 128, b * SEQ + orow0, sb + BAR_CF + i * 8);
            }
            for (int i = 0; i < 2 * C_STAGES; i++) {
                const int st = i >> 1, b = i & 1;
                const uint32_t s0 = sb + st * C_STAGE_BYTES + b * 24576;
                mbar_wait(sb + BAR_CE + i * 8, 0);
                mbar_expect_tx(sb + BAR_CF + i * 8, 24576);
                tma_2d(s0 + 8192, &maps.wo[b], ocol0, st * 128 + 64, sb + BAR_CF + i * 8);
                tma_2d(s0 + 16384, &maps.wo[b], ocol0 + 64, st * 128 + 64, sb + BAR_CF + i * 8);
                if (i == 0) {
                    spin_until(&g_ctr[2 + mb * 4 + 2 + (nb >> 2)], 32);
                    fence_async();
                }
                tma_2d(s0, &maps.o, st * 128 + 64, b * SEQ + orow0, sb + BAR_CF + i * 8);
            }
            __threadfence();
            if (atomicAdd(&g_ctr[66], 1u) == 127u) {
                for (int i = 0; i < 67; i++) g_ctr[i] = 0u;
            }
        }
    } else if (wg < 2) {
        const int warp = tid >> 5, lane = tid & 31;
        float acc[64];
#pragma unroll
        for (int i = 0; i < 64; i++) acc[i] = 0.f;
        fence_regs<64>(acc);
        const int r = lane >> 2, c = lane & 3;
        const int lrow = (warp & 3) * 16 + r;
        float g0 = 0.f, g1 = 0.f;
#pragma unroll
        for (int kb = 0; kb < 8; kb++) {
            const int st = kb % C_STAGES;
            const uint32_t s0 = sb + st * C_STAGE_BYTES + wg * 24576;
            mbar_wait_u(sb + BAR_CF + (st * 2 + wg) * 8, kb >= C_STAGES ? 1 : 0);
            if (kb == 0) {
                ts_min(8); ts_max(24);
                g0 = __ldcg(g_gate + orow0 + lrow);
                g1 = __ldcg(g_gate + orow0 + lrow + 8);
            }
            const uint64_t ad = make_desc(s0, 16, 1024, 1);
            const uint64_t bd = make_desc(s0 + 8192, 8192, 1024, 1);
            wg_fence();
#pragma unroll
            for (int kk = 0; kk < 4; kk++) mma_n128_ss(acc, ad + kk * 2, bd + kk * 128);
            wg_commit();
            if (kb >= 1 && kb <= C_STAGES) {
                wg_wait<1>();
                if (lane == 0) mbar_arrive(sb + BAR_CE + ((kb - 1) * 2 + wg) * 8);
            }
        }
        wg_wait<0>();
        fence_regs<64>(acc);
        ts_min(9); ts_max(25);
        if (wg) { g0 = bf_round(1.f - g0); g1 = bf_round(1.f - g1); }
        uint32_t t[32];
#pragma unroll
        for (int j = 0; j < 16; j++) {
            t[2 * j] = pack_bf16(g0 * bf_round(acc[4 * j]), g0 * bf_round(acc[4 * j + 1]));
            t[2 * j + 1] = pack_bf16(g1 * bf_round(acc[4 * j + 2]), g1 * bf_round(acc[4 * j + 3]));
        }
        uint32_t* xch = (uint32_t*)(smem + SM_XCH);
        const int lt = tid & 127;
#pragma unroll
        for (int j = 0; j < 16; j++) xch[(wg * 16 + j) * 128 + lt] = wg ? t[j] : t[16 + j];
        asm volatile("bar.sync 1, 256;" ::: "memory");
        unsigned char* ot = smem + wg * 16384;
#pragma unroll
        for (int j = 0; j < 16; j++) {
            const uint32_t mine = wg ? t[16 + j] : t[j];
            const uint32_t other = xch[((wg ^ 1) * 16 + j) * 128 + lt];
            const uint32_t v = pack_bf16(bf_lo(mine) + bf_lo(other), bf_hi(mine) + bf_hi(other));
            *(uint32_t*)(ot + (lrow + (j & 1) * 8) * 144 + (j >> 1) * 16 + c * 4) = v;
        }
        asm volatile("bar.sync %0, 128;" ::"r"(wg + 2) : "memory");
#pragma unroll
        for (int i = 0; i < 4; i++) {
            const int idx = i * 128 + lt, row = idx >> 3, ch = idx & 7;
            const uint4 v = *(const uint4*)(ot + row * 144 + ch * 16);
            *(uint4*)(out + (size_t)(orow0 + row) * DM + ocol0 + wg * 64 + ch * 8) = v;
        }
        ts_min(10); ts_max(26);
    }
}

typedef CUresult (*EncodeFn)(CUtensorMap*, CUtensorMapDataType, cuuint32_t, void*, const cuuint64_t*, const cuuint64_t*, const cuuint32_t*,
                             const cuuint32_t*, CUtensorMapInterleave, CUtensorMapSwizzle, CUtensorMapL2promotion, CUtensorMapFloatOOBfill);

static void encode_2d(EncodeFn fn, CUtensorMap* m, const void* ptr, uint64_t inner, uint64_t outer, uint32_t box_inner, uint32_t box_outer,
                      CUtensorMapSwizzle swz = CU_TENSOR_MAP_SWIZZLE_128B) {
    cuuint64_t dims[2] = {inner, outer};
    cuuint64_t strides[1] = {inner * 2};
    cuuint32_t box[2] = {box_inner, box_outer};
    cuuint32_t es[2] = {1, 1};
    fn(m, CU_TENSOR_MAP_DATA_TYPE_BFLOAT16, 2, (void*)ptr, dims, strides, box, es, CU_TENSOR_MAP_INTERLEAVE_NONE, swz,
       CU_TENSOR_MAP_L2_PROMOTION_L2_256B, CU_TENSOR_MAP_FLOAT_OOB_FILL_NONE);
}

extern "C" void kernel_launch(void* const* d_in, const int* in_sizes, int n_in, void* d_out, int out_size) {
    (void)in_sizes; (void)n_in; (void)out_size;
    static Maps m;
    static const void* cached[11] = {0};
    static bool attr_done = false;
    bool same = true;
    for (int i = 0; i < 11; i++) same = same && (cached[i] == d_in[i]);
    if (!same || !attr_done) {
        void* fnp = nullptr;
        cudaDriverEntryPointQueryResult qr;
        cudaGetDriverEntryPoint("cuTensorMapEncodeTiled", &fnp, cudaEnableDefault, &qr);
        EncodeFn fn = (EncodeFn)fnp;
        void* po = nullptr;
        cudaGetSymbolAddress(&po, g_O);
        encode_2d(fn, &m.x, d_in[0], DM, SEQ, 64, 128);
        encode_2d(fn, &m.wq[0], d_in[1], DM, DM, 64, 64);
        encode_2d(fn, &m.wq[1], d_in[6], DM, DM, 64, 64);
        encode_2d(fn, &m.wkv[0], d_in[2], 16, DM, 8, 256, CU_TENSOR_MAP_SWIZZLE_NONE);
        encode_2d(fn, &m.wkv[1], d_in[3], 16, DM, 8, 256, CU_TENSOR_MAP_SWIZZLE_NONE);
        encode_2d(fn, &m.wkv[2], d_in[7], 16, DM, 8, 256, CU_TENSOR_MAP_SWIZZLE_NONE);
        encode_2d(fn, &m.wkv[3], d_in[8], 16, DM, 8, 256, CU_TENSOR_MAP_SWIZZLE_NONE);
        encode_2d(fn, &m.o, po, DM, 2 * SEQ, 64, 64);
        encode_2d(fn, &m.wo[0], d_in[4], DM, DM, 64, 64);
        encode_2d(fn, &m.wo[1], d_in[9], DM, DM, 64, 64);
        cudaFuncSetAttribute(fused_kernel, cudaFuncAttributeMaxDynamicSharedMemorySize, SMEM_TOTAL);
        for (int i = 0; i < 11; i++) cached[i] = d_in[i];
        attr_done = true;
    }
    cudaLaunchAttribute at[1];
    at[0].id = cudaLaunchAttributeCooperative;
    at[0].val.cooperative = 1;
    cudaLaunchConfig_t cfg = {};
    cfg.stream = cudaStreamPerThread;
    cfg.attrs = at;
    cfg.numAttrs = 1;
    cfg.gridDim = dim3(128);
    cfg.blockDim = dim3(512);
    cfg.dynamicSmemBytes = SMEM_TOTAL;
    cudaLaunchKernelEx(&cfg, fused_kernel, m, (const bf16*)d_in[0], (const bf16*)d_in[10], (const bf16*)d_in[1], (const bf16*)d_in[6],
                       (const bf16*)d_in[4], (const bf16*)d_in[9], (bf16*)d_out);
}
```

```cpp
#include <cuda_runtime.h>
#include <cuda_bf16.h>
#include <cuda.h>
#include <stdint.h>

typedef __nv_bfloat16 bf16;

#define CTR_PAD 32
#define SEPQK 1
#define SEQ 2048
#define DM 512
#define ROWS 65536

__device__ __align__(1024) bf16 g_KV[2 * 4 * SEQ * 8];
__device__ __align__(1024) bf16 g_O[2 * ROWS * 16];
__device__ float g_gate[SEQ];
__device__ __align__(128) unsigned char g_qx[128 * 2048];
__device__ __align__(128) float4 g_px[128 * 3 * 128];
__device__ __align__(16) unsigned int g_flag[256];
#define SPLIT_TILE 15
#define NSPLIT 5
__device__ __align__(16) float g_nrm[512];
__device__ __align__(128) unsigned int g_ctr[19 * CTR_PAD];
#define CTR(i) (g_ctr + (i) * CTR_PAD)

#define ts_min(i)
#define ts_max(i)
__device__ __forceinline__ uint32_t smem_u32(const void* p) { return (uint32_t)__cvta_generic_to_shared(p); }
__device__ __forceinline__ uint64_t make_desc(uint32_t saddr, uint32_t lbo, uint32_t sbo, uint32_t swz) {
    uint64_t d = 0;
    d |= (uint64_t)((saddr & 0x3FFFF) >> 4);
    d |= (uint64_t)((lbo & 0x3FFFF) >> 4) << 16;
    d |= (uint64_t)((sbo & 0x3FFFF) >> 4) << 32;
    d |= (uint64_t)swz << 62;
    return d;
}
__device__ __forceinline__ void wg_fence() { asm volatile("wgmma.fence.sync.aligned;" ::: "memory"); }
__device__ __forceinline__ void wg_commit() { asm volatile("wgmma.commit_group.sync.aligned;" ::: "memory"); }
template <int N> __device__ __forceinline__ void wg_wait() { asm volatile("wgmma.wait_group.sync.aligned %0;" ::"n"(N) : "memory"); }
template <int N> __device__ __forceinline__ void fence_regs(float* d) {
#pragma unroll
    for (int i = 0; i < N; i++) asm volatile("" : "+f"(d[i])::"memory");
}
__device__ __forceinline__ void mbar_init(uint32_t bar, uint32_t cnt) { asm volatile("mbarrier.init.shared::cta.b64 [%0], %1;" ::"r"(bar), "r"(cnt)); }
__device__ __forceinline__ void mbar_expect_tx(uint32_t bar, uint32_t bytes) {
    asm volatile("mbarrier.arrive.expect_tx.shared::cta.b64 _, [%0], %1;" ::"r"(bar), "r"(bytes) : "memory");
}
__device__ __forceinline__ void mbar_arrive(uint32_t bar) { asm volatile("mbarrier.arrive.shared::cta.b64 _, [%0];" ::"r"(bar) : "memory"); }
__device__ __forceinline__ void mbar_wait(uint32_t bar, uint32_t parity) {
    asm volatile(
        "{\n.reg .pred p;\n"
        "WAIT_LOOP:\n"
        "mbarrier.try_wait.parity.shared::cta.b64 p, [%0], %1;\n"
        "@p bra DONE;\n"
        "bra WAIT_LOOP;\n"
        "DONE:\n}" ::"r"(bar), "r"(parity) : "memory");
}
__device__ __forceinline__ void mbar_wait_u(uint32_t bar, uint32_t parity) {
    uint32_t ok;
    do {
        asm volatile(
            "{\n.reg .pred p;\nmbarrier.try_wait.parity.shared::cta.b64 p, [%1], %2;\nselp.u32 %0, 1, 0, p;\n}"
            : "=r"(ok) : "r"(bar), "r"(parity) : "memory");
    } while (!__all_sync(0xffffffffu, ok));
}
__device__ __forceinline__ void bulk_g2s(uint32_t dst, const void* src, uint32_t bytes, uint32_t bar) {
    asm volatile("cp.async.bulk.shared::cluster.global.mbarrier::complete_tx::bytes [%0], [%1], %2, [%3];" ::"r"(dst), "l"(src), "r"(bytes), "r"(bar) : "memory");
}
__device__ __forceinline__ void tma_2d(uint32_t dst, const CUtensorMap* map, int c0, int c1, uint32_t bar) {
    asm volatile("cp.async.bulk.tensor.2d.shared::cluster.global.mbarrier::complete_tx::bytes [%0], [%1, {%3, %4}], [%2];" ::"r"(dst), "l"(map), "r"(bar), "r"(c0), "r"(c1) : "memory");
}
__device__ __forceinline__ void l2_prefetch(const void* p, uint32_t bytes) {
    asm volatile("cp.async.bulk.prefetch.L2.global [%0], %1;" ::"l"(p), "r"(bytes) : "memory");
}
__device__ __forceinline__ void pdl_launch() { asm volatile("griddepcontrol.launch_dependents;" ::: "memory"); }
__device__ __forceinline__ void pdl_wait() { asm volatile("griddepcontrol.wait;" ::: "memory"); }
__device__ __forceinline__ void fence_async() { asm volatile("fence.proxy.async;" ::: "memory"); }
__device__ __forceinline__ uint32_t pack_bf16(float lo, float hi) {
    uint32_t r;
    asm("cvt.rn.bf16x2.f32 %0, %1, %2;" : "=r"(r) : "f"(hi), "f"(lo));
    return r;
}
__device__ __forceinline__ float bf_lo(uint32_t u) { return __uint_as_float(u << 16); }
__device__ __forceinline__ float bf_hi(uint32_t u) { return __uint_as_float(u & 0xFFFF0000u); }
__device__ __forceinline__ float bf_round(float x) { return __bfloat162float(__float2bfloat16_rn(x)); }

#define A8(b) "+f"(d[b + 0]), "+f"(d[b + 1]), "+f"(d[b + 2]), "+f"(d[b + 3]), "+f"(d[b + 4]), "+f"(d[b + 5]), "+f"(d[b + 6]), "+f"(d[b + 7])
#define W8(b) "=f"(d[b + 0]), "=f"(d[b + 1]), "=f"(d[b + 2]), "=f"(d[b + 3]), "=f"(d[b + 4]), "=f"(d[b + 5]), "=f"(d[b + 6]), "=f"(d[b + 7])

__device__ __forceinline__ void mma_n8_ss(float* d, uint64_t ad, uint64_t bd) {
    asm volatile("wgmma.mma_async.sync.aligned.m64n8k16.f32.bf16.bf16 {%0,%1,%2,%3}, %4, %5, 1, 1, 1, 0, 1;"
                 : "+f"(d[0]), "+f"(d[1]), "+f"(d[2]), "+f"(d[3])
                 : "l"(ad), "l"(bd));
}
__device__ __forceinline__ void mma_n128_ss(float* d, uint64_t ad, uint64_t bd) {
    asm volatile(
        "wgmma.mma_async.sync.aligned.m64n128k16.f32.bf16.bf16 "
        "{%0,%1,%2,%3,%4,%5,%6,%7,%8,%9,%10,%11,%12,%13,%14,%15,%16,%17,%18,%19,%20,%21,%22,%23,%24,%25,%26,%27,%28,%29,%30,%31,"
        "%32,%33,%34,%35,%36,%37,%38,%39,%40,%41,%42,%43,%44,%45,%46,%47,%48,%49,%50,%51,%52,%53,%54,%55,%56,%57,%58,%59,%60,%61,%62,%63}, "
        "%64, %65, 1, 1, 1, 0, 1;"
        : A8(0), A8(8), A8(16), A8(24), A8(32), A8(40), A8(48), A8(56)
        : "l"(ad), "l"(bd));
}
__device__ __forceinline__ void qk_n64(float* d, const uint32_t* a, uint64_t bd) {
    asm volatile(
        "wgmma.mma_async.sync.aligned.m64n64k16.f32.bf16.bf16 "
        "{%0,%1,%2,%3,%4,%5,%6,%7,%8,%9,%10,%11,%12,%13,%14,%15,%16,%17,%18,%19,%20,%21,%22,%23,%24,%25,%26,%27,%28,%29,%30,%31}, "
        "{%32,%33,%34,%35}, %36, 0, 1, 1, 0;"
        : W8(0), W8(8), W8(16), W8(24)
        : "r"(a[0]), "r"(a[1]), "r"(a[2]), "r"(a[3]), "l"(bd));
}
__device__ __forceinline__ void pv_n24(float* d, const uint32_t* a, uint64_t bd) {
    asm volatile(
        "wgmma.mma_async.sync.aligned.m64n24k16.f32.bf16.bf16 {%0,%1,%2,%3,%4,%5,%6,%7,%8,%9,%10,%11}, {%12,%13,%14,%15}, %16, 1, 1, 1, 1;"
        : A8(0), "+f"(d[8]), "+f"(d[9]), "+f"(d[10]), "+f"(d[11])
        : "r"(a[0]), "r"(a[1]), "r"(a[2]), "r"(a[3]), "l"(bd));
}

__device__ __forceinline__ float ex2(float x) {
    float e;
    asm("ex2.approx.ftz.f32 %0, %1;" : "=f"(e) : "f"(x));
    return e;
}
__device__ __forceinline__ uint32_t exp_pair_mufu(float x0, float x1) { return pack_bf16(ex2(x0), ex2(x1)); }

#define MAGIC0 (98304.0f + 127.0f - 75.0f / 128.0f)
#define MAGIC1 (98304.0f + 127.0f - 75.0f / 128.0f - 143.5f)
template <int PRM>
__device__ __forceinline__ uint32_t exp_pair_poly(float x0, float x1, uint32_t c3f) {
    float t0 = x0 + MAGIC0;
    float t1 = x1 + (PRM ? MAGIC0 : MAGIC1);
    uint32_t L, y2, E, r;
    if (PRM)
        asm("prmt.b32 %0, %1, %2, 0x5410;" : "=r"(L) : "r"(__float_as_uint(t0)), "r"(__float_as_uint(t1)));
    else
        L = __float_as_uint(t1) * 65536u + __float_as_uint(t0);
    asm("lop3.b32 %0, %1, 0x007F007F, %2, 0xEA;" : "=r"(y2) : "r"(L), "r"(c3f));
    E = L & 0x7F807F80u;
    asm("fma.rn.bf16x2 %0, %1, %2, %3;" : "=r"(r) : "r"(L), "r"(y2), "r"(E));
    return r;
}
#define EXP_MASK 0x2525u
template <int BASE>
__device__ __forceinline__ void exp_half(const float* s, uint32_t* p, uint32_t c3f) {
#pragma unroll
    for (int i = 0; i < 8; i++) {
        if ((EXP_MASK >> (BASE + i)) & 1) p[i] = exp_pair_mufu(s[2 * i], s[2 * i + 1]);
        else p[i] = exp_pair_poly<0>(s[2 * i], s[2 * i + 1], c3f);
    }
}

struct Maps {
    CUtensorMap x;
    CUtensorMap wq[2];
    CUtensorMap wkv[4];
    CUtensorMap o;
    CUtensorMap wo[2];
};
#define SM_X 20480
#define SM_WKV 151552
#define SM_WQ 159744
#define CHUNK_BYTES 20480
#define SM_Q 163840
#define C_STAGES 4
#define C_STAGE_BYTES 49152
#define SM_XCH 196608
#define SM_BAR 225280
#define BAR_X (SM_BAR)
#define BAR_KV (SM_BAR + 64)
#define BAR_CF (SM_BAR + 128)
#define BAR_CE (SM_BAR + 192)
#define BAR_WF (SM_BAR + 256)
#define BAR_WE (SM_BAR + 288)
#define BAR_WKV (SM_BAR + 320)
#define SM_MISC (SM_BAR + 384)
#define SMEM_TOTAL (SM_BAR + 1024 + 1024)

__device__ __forceinline__ void spin_until(const unsigned int* ctr, unsigned int target) {
    unsigned int v;
    for (unsigned int it = 0; it < (1u << 26); it++) {
        asm volatile("ld.acquire.gpu.global.u32 %0, [%1];" : "=r"(v) : "l"(ctr) : "memory");
        if (v >= target) return;
    }
    __trap();
}
__device__ __forceinline__ void signal(unsigned int* ctr) {
    asm volatile("red.release.gpu.global.add.u32 [%0], 1;" ::"l"(ctr) : "memory");
}

__device__ __forceinline__ void attn_tile_slow(const uint32_t* qq, uint64_t kd0, uint64_t vd0, float* o, float* s, uint32_t* p) {
    float m0 = -INFINITY, m1 = -INFINITY;
#pragma unroll 1
    for (int ch = 0; ch < 32; ch++) {
        wg_fence();
        qk_n64(s, qq, kd0 + (uint64_t)((ch >> 2) * 1280 + (ch & 3) * 64));
        wg_commit();
        wg_wait<0>();
        fence_regs<32>(s);
#pragma unroll
        for (int j = 0; j < 8; j++) {
            m0 = fmaxf(m0, fmaxf(s[4 * j], s[4 * j + 1]));
            m1 = fmaxf(m1, fmaxf(s[4 * j + 2], s[4 * j + 3]));
        }
    }
    m0 = fmaxf(m0, __shfl_xor_sync(0xffffffffu, m0, 1));
    m1 = fmaxf(m1, __shfl_xor_sync(0xffffffffu, m1, 1));
    m0 = fmaxf(m0, __shfl_xor_sync(0xffffffffu, m0, 2));
    m1 = fmaxf(m1, __shfl_xor_sync(0xffffffffu, m1, 2));
#pragma unroll 1
    for (int ch = 0; ch < 32; ch++) {
        wg_fence();
        qk_n64(s, qq, kd0 + (uint64_t)((ch >> 2) * 1280 + (ch & 3) * 64));
        wg_commit();
        wg_wait<0>();
        fence_regs<32>(s);
#pragma unroll
        for (int j = 0; j < 8; j++) {
            p[2 * j] = exp_pair_mufu(s[4 * j] - m0, s[4 * j + 1] - m0);
            p[2 * j + 1] = exp_pair_mufu(s[4 * j + 2] - m1, s[4 * j + 3] - m1);
        }
        wg_fence();
#pragma unroll
        for (int j = 0; j < 4; j++) pv_n24(o, p + 4 * j, vd0 + (uint64_t)((ch >> 2) * 1280 + (ch & 3) * 64 + 16 * j));
        wg_commit();
        wg_wait<0>();
        fence_regs<12>(o);
    }
}

#define TILE_OF(w, t) ((w) * 4 + (t))
#define UNIT_CTA(t) (helper ? (((wg * 8 + (t)) >> 2) * 2 + (int)(blockIdx.x & 1)) * 8 + br * 4 + ((t) & 3) : (int)blockIdx.x)
#define LOAD_Q(t)                                                                                                        \
    {                                                                                                                    \
        const unsigned char* qp = (helper ? g_qx + cta * 2048 : smem + SM_Q + TILE_OF(wg, t) * 2048) + ((tid >> 5) & 3) * 512 + (tid & 31) * 8; \
        asm volatile("ld.volatile.v2.u32 {%0, %1}, [%2];" : "=r"(q[0]), "=r"(q[2]) : "l"(qp) : "memory");                \
        asm volatile("ld.volatile.v2.u32 {%0, %1}, [%2];" : "=r"(q[1]), "=r"(q[3]) : "l"(qp + 256) : "memory");          \
    }
__device__ __forceinline__ void finish() {
    __threadfence();
    if (atomicAdd(CTR(18), 1u) == gridDim.x - 1) {
        for (int i = 0; i < 19; i++) *CTR(i) = 0u;
        for (int i = 0; i < 256; i += 4) *(uint4*)(g_flag + i) = make_uint4(0, 0, 0, 0);
    }
}
__device__ __forceinline__ void store_o(const float* o, int cta, int tile) {
    const int mb = cta >> 3, nb = cta & 7, br = nb >> 2;
    int tid2;
    asm volatile("mov.u32 %0, %%tid.x;" : "=r"(tid2));
    const int lane = tid2 & 31;
    const float l0 = __shfl_sync(0xffffffffu, o[8], lane & ~3);
    const float l1 = __shfl_sync(0xffffffffu, o[10], lane & ~3);
    const float i0 = 1.f / l0, i1 = 1.f / l1;
    const uint32_t row = (uint32_t)(br * SEQ + mb * 128 + (tile & 1) * 64 + ((tid2 >> 5) & 3) * 16 + (lane >> 2));
    bf16* op = g_O + row * DM + ((nb & 3) * 8 + (tile >> 1)) * 16 + (lane & 3) * 2;
    *(uint32_t*)(op) = pack_bf16(o[0] * i0, o[1] * i0);
    *(uint32_t*)(op + 8 * DM) = pack_bf16(o[2] * i1, o[3] * i1);
    *(uint32_t*)(op + 8) = pack_bf16(o[4] * i0, o[5] * i0);
    *(uint32_t*)(op + 8 * DM + 8) = pack_bf16(o[6] * i1, o[7] * i1);
}

__global__ void __launch_bounds__(512, 1) fused_kernel(const __grid_constant__ Maps maps, const bf16* __restrict__ x, const bf16* __restrict__ gate_w,
                                                        const bf16* __restrict__ wqa, const bf16* __restrict__ wqb, const bf16* __restrict__ woa,
                                                        const bf16* __restrict__ wob, bf16* __restrict__ out) {
    const bool split = gridDim.x > 128;
    const bool helper = blockIdx.x >= 128;
    extern __shared__ unsigned char smem_raw[];
    const uint32_t sb = (smem_u32(smem_raw) + 1023) & ~1023u;
    unsigned char* smem = smem_raw + (sb - smem_u32(smem_raw));
    const int tid = threadIdx.x;
    const int wg = __shfl_sync(0xffffffffu, tid >> 7, 0);
    const int mb = blockIdx.x >> 3, nb = blockIdx.x & 7;
    const int br = helper ? (int)((blockIdx.x >> 1) & 1) : nb >> 2;
    ts_min(0); ts_max(16);
    if (tid == 384 && !helper) {
        for (int i = 0; i < 8; i++) mbar_init(sb + BAR_X + i * 8, 1);
        mbar_init(sb + BAR_WKV, 1);
        asm volatile("fence.mbarrier_init.release.cluster;" ::: "memory");
        mbar_expect_tx(sb + BAR_WKV, 8192);
        tma_2d(sb + SM_WKV, &maps.wkv[nb >> 1], (nb & 1) * 8, 0, sb + BAR_WKV);
        tma_2d(sb + SM_WKV + 4096, &maps.wkv[nb >> 1], (nb & 1) * 8, 256, sb + BAR_WKV);
        for (int kb = 0; kb < 8; kb++) {
            mbar_expect_tx(sb + BAR_X + kb * 8, 16384);
            tma_2d(sb + SM_X + kb * 16384, &maps.x, kb * 64, mb * 128, sb + BAR_X + kb * 8);
        }
    }
    if (tid == 352) asm volatile("prefetch.tensormap [%0];" ::"l"(&maps.x) : "memory");
    if (tid == 0) {
        for (int i = 0; i < 8; i++) {
            mbar_init(sb + BAR_KV + i * 8, 1);
            mbar_init(sb + BAR_CF + i * 8, 1);
            mbar_init(sb + BAR_CE + i * 8, 4);
        }
        for (int i = 0; i < 4; i++) {
            mbar_init(sb + BAR_WF + i * 8, 1);
            mbar_init(sb + BAR_WE + i * 8, 8);
        }
        asm volatile("fence.mbarrier_init.release.cluster;" ::: "memory");
    }
    if (tid == 416 && !helper) {
        l2_prefetch(wqa + (size_t)blockIdx.x * 2048, 4096);
        l2_prefetch(wqb + (size_t)blockIdx.x * 2048, 4096);
        asm volatile("prefetch.tensormap [%0];" ::"l"(&maps.wq[br]) : "memory");
        asm volatile("prefetch.tensormap [%0];" ::"l"(&maps.o) : "memory");
        asm volatile("prefetch.tensormap [%0];" ::"l"(&maps.wo[0]) : "memory");
        asm volatile("prefetch.tensormap [%0];" ::"l"(&maps.wo[1]) : "memory");
    }
    __syncthreads();

    const unsigned char* kv_src = (const unsigned char*)g_KV + (size_t)br * 131072;
    if (helper) {
#pragma unroll
        for (int i = 0; i < 4; i++) *(uint4*)(smem + (2 * i + (tid >> 8)) * CHUNK_BYTES + 16384 + (tid & 255) * 16) = make_uint4(0x00003F80u, 0, 0, 0);
        asm volatile("fence.proxy.async.shared::cta;" ::: "memory");
    }
    if (helper && wg < 3) {
    } else if (wg < 2) {
        const int warp = tid >> 5, lane = tid & 31;
        float acc[64];
#pragma unroll
        for (int i = 0; i < 64; i++) acc[i] = 0.f;
        fence_regs<64>(acc);
        asm volatile("bar.sync 3, 384;" ::: "memory");
#pragma unroll
        for (int kb = 0; kb < 8; kb++) {
            const int st = kb & 3;
            mbar_wait_u(sb + BAR_WF + st * 8, kb >> 2);
            if (kb == 0) { ts_min(12); ts_max(28); }
            const uint64_t ad = make_desc(sb + SM_X + kb * 16384 + wg * 8192, 16, 1024, 1);
            const uint64_t bd = make_desc(sb + SM_WQ + st * 16384, 8192, 1024, 1);
            wg_fence();
#pragma unroll
            for (int kk = 0; kk < 4; kk++) mma_n128_ss(acc, ad + kk * 2, bd + kk * 128);
            wg_commit();
            if (kb >= 1 && kb <= 4) {
                wg_wait<1>();
                if (lane == 0) mbar_arrive(sb + BAR_WE + (kb - 1) * 8);
            }
        }
        wg_wait<0>();
        fence_regs<64>(acc);
        ts_min(1); ts_max(17);
        asm volatile("bar.sync 1, 384;" ::: "memory");
        const int r = lane >> 2, c = lane & 3;
        const float qs = 0.25f * 1.4426950408889634f;
        unsigned char* qp = smem + SM_Q + wg * 2048 + ((warp & 3) * 16 + r) * 32 + c * 8;
#pragma unroll
        for (int h = 0; h < 8; h++) {
            const float* a = acc + h * 8;
            *(uint2*)(qp + h * 4096) = make_uint2(pack_bf16(a[0] * qs, a[1] * qs), pack_bf16(a[4] * qs, a[5] * qs));
            *(uint2*)(qp + h * 4096 + 256) = make_uint2(pack_bf16(a[2] * qs, a[3] * qs), pack_bf16(a[6] * qs, a[7] * qs));
        }
        ts_min(2); ts_max(18);
    } else if (wg == 2) {
        const int warp = (tid >> 5) & 3, lane = tid & 31;
        float a0[4] = {0.f, 0.f, 0.f, 0.f}, a1[4] = {0.f, 0.f, 0.f, 0.f};
        fence_regs<4>(a0);
        fence_regs<4>(a1);
        *(uint4*)(smem + 16384 + (tid & 127) * 16) = make_uint4(0x00003F80u, 0, 0, 0);
        *(uint4*)(smem + 18432 + (tid & 127) * 16) = make_uint4(0x00003F80u, 0, 0, 0);
        mbar_wait_u(sb + BAR_WKV, 0);
#pragma unroll
        for (int kb = 0; kb < 8; kb++) {
            mbar_wait_u(sb + BAR_X + kb * 8, 0);
            const uint64_t ad = make_desc(sb + SM_X + kb * 16384, 16, 1024, 1);
            const uint64_t bd = make_desc(sb + SM_WKV + kb * 1024, 128, 128, 0);
            wg_fence();
#pragma unroll
            for (int kk = 0; kk < 4; kk++) {
                mma_n8_ss(a0, ad + kk * 2, bd + kk * 16);
                mma_n8_ss(a1, ad + 512 + kk * 2, bd + kk * 16);
            }
            wg_commit();
        }
        wg_wait<0>();
        fence_regs<4>(a0);
        fence_regs<4>(a1);
        asm volatile("bar.arrive 3, 384;" ::: "memory");
        ts_min(14); ts_max(30);
        const int r = lane >> 2, c = lane & 3;
        const int row = mb * 128 + warp * 16 + r;
        const uint32_t k0 = pack_bf16(a0[0], a0[1]), k1 = pack_bf16(a0[2], a0[3]);
        const uint32_t k2 = pack_bf16(a1[0], a1[1]), k3 = pack_bf16(a1[2], a1[3]);
        bf16* kvp = g_KV + (size_t)br * 65536 + (row >> 8) * 8192 + (nb & 3) * 2048 + (row & 255) * 8 + 2 * c;
        *(uint32_t*)kvp = k0;
        *(uint32_t*)(kvp + 64) = k1;
        *(uint32_t*)(kvp + 512) = k2;
        *(uint32_t*)(kvp + 576) = k3;
        unsigned int mu;
        if (((nb >> 1) & 1) == 0) {
            float n0 = bf_lo(k0) * bf_lo(k0) + bf_hi(k0) * bf_hi(k0);
            float n1 = bf_lo(k1) * bf_lo(k1) + bf_hi(k1) * bf_hi(k1);
            float n2 = bf_lo(k2) * bf_lo(k2) + bf_hi(k2) * bf_hi(k2);
            float n3 = bf_lo(k3) * bf_lo(k3) + bf_hi(k3) * bf_hi(k3);
#pragma unroll
            for (int sft = 1; sft <= 2; sft <<= 1) {
                n0 += __shfl_xor_sync(0xffffffffu, n0, sft);
                n1 += __shfl_xor_sync(0xffffffffu, n1, sft);
                n2 += __shfl_xor_sync(0xffffffffu, n2, sft);
                n3 += __shfl_xor_sync(0xffffffffu, n3, sft);
            }
            mu = max(max(__float_as_uint(n0), __float_as_uint(n1)), max(__float_as_uint(n2), __float_as_uint(n3)));
        } else {
            mu = max(max(max((k0 << 16) & 0x7FFFFFFFu, k0 & 0x7FFF0000u), max((k1 << 16) & 0x7FFFFFFFu, k1 & 0x7FFF0000u)),
                     max(max((k2 << 16) & 0x7FFFFFFFu, k2 & 0x7FFF0000u), max((k3 << 16) & 0x7FFFFFFFu, k3 & 0x7FFF0000u)));
        }
        mu = __reduce_max_sync(0xffffffffu, mu);
        __syncwarp();
        if (lane == 0) {
            g_nrm[(nb * 16 + mb) * 4 + warp] = __uint_as_float(mu);
            signal(CTR(br));
            ts_min(13); ts_max(29);
        }
        asm volatile("bar.sync 1, 384;" ::: "memory");
#pragma unroll
        for (int i = 1; i < 8; i++) {
            *(uint4*)(smem + i * CHUNK_BYTES + 16384 + (tid & 127) * 16) = make_uint4(0x00003F80u, 0, 0, 0);
            *(uint4*)(smem + i * CHUNK_BYTES + 18432 + (tid & 127) * 16) = make_uint4(0x00003F80u, 0, 0, 0);
        }
        asm volatile("fence.proxy.async.shared::cta;" ::: "memory");
    } else {
        const int lane = tid & 31, w = (tid >> 5) & 3;
        if (w == 0) {
            if (lane == 0) {
                if (!helper) {
                mbar_wait(sb + BAR_X + 56, 0);
                ts_min(11); ts_max(27);
                for (int st = 0; st < 4; st++) {
                    mbar_expect_tx(sb + BAR_WF + st * 8, 16384);
                    tma_2d(sb + SM_WQ + st * 16384, &maps.wq[br], (nb & 3) * 128, st * 64, sb + BAR_WF + st * 8);
                    tma_2d(sb + SM_WQ + st * 16384 + 8192, &maps.wq[br], (nb & 3) * 128 + 64, st * 64, sb + BAR_WF + st * 8);
                }
                for (int st = 0; st < 4; st++) {
                    mbar_wait(sb + BAR_WE + st * 8, 0);
                    mbar_expect_tx(sb + BAR_WF + st * 8, 16384);
                    tma_2d(sb + SM_WQ + st * 16384, &maps.wq[br], (nb & 3) * 128, (st + 4) * 64, sb + BAR_WF + st * 8);
                    tma_2d(sb + SM_WQ + st * 16384 + 8192, &maps.wq[br], (nb & 3) * 128 + 64, (st + 4) * 64, sb + BAR_WF + st * 8);
                }
                l2_prefetch(woa + (size_t)blockIdx.x * 2048, 4096);
                l2_prefetch(wob + (size_t)blockIdx.x * 2048, 4096);
                }
                spin_until(CTR(br), 256);
                fence_async();
                ts_min(4); ts_max(20);
                mbar_expect_tx(sb + BAR_KV, 16384);
                bulk_g2s(sb, kv_src, 16384, sb + BAR_KV);
            }
            __syncwarp();
            const uint4 hk = __ldcg((const uint4*)g_nrm + br * 64 + lane);
            const uint4 hv = __ldcg((const uint4*)g_nrm + br * 64 + 32 + lane);
            unsigned int h = max(max(hk.x, hk.y), max(hk.z, hk.w));
            const unsigned int nv = max(max(hv.x, hv.y), max(hv.z, hv.w));
#pragma unroll
            for (int sft = 8; sft > 0; sft >>= 1) h = max(h, __shfl_xor_sync(0xffffffffu, h, sft));
            float kmax2 = __uint_as_float(h) + __uint_as_float(__shfl_xor_sync(0xffffffffu, h, 16));
            const float vmax = __uint_as_float(__reduce_max_sync(0xffffffffu, nv));
            if (!(vmax <= 1.0e15f)) kmax2 = __uint_as_float(0x7FC00000u);
            if (lane == 0) *(volatile float*)(smem + SM_MISC + 4) = kmax2;
        } else if (!helper) {
            const uint4* gw = (const uint4*)(gate_w + lane * 16);
            const uint4 w0 = __ldg(gw), w1 = __ldg(gw + 1);
            const uint32_t wv[8] = {w0.x, w0.y, w0.z, w0.w, w1.x, w1.y, w1.z, w1.w};
            uint4 xa[6][2];
#pragma unroll
            for (int rr = 0; rr < 6; rr++) {
                const int lr = min(w - 1 + rr * 3, 15);
                const uint4* xp = (const uint4*)(x + (size_t)(blockIdx.x * 16 + lr) * DM + lane * 16);
                xa[rr][0] = __ldg(xp);
                xa[rr][1] = __ldg(xp + 1);
            }
#pragma unroll
            for (int rr = 0; rr < 6; rr++) {
                const uint32_t xv[8] = {xa[rr][0].x, xa[rr][0].y, xa[rr][0].z, xa[rr][0].w, xa[rr][1].x, xa[rr][1].y, xa[rr][1].z, xa[rr][1].w};
                float sum = 0.f;
#pragma unroll
                for (int i = 0; i < 8; i++) {
                    sum += bf_round(bf_lo(xv[i]) * bf_lo(wv[i]));
                    sum += bf_round(bf_hi(xv[i]) * bf_hi(wv[i]));
                }
#pragma unroll
                for (int o = 16; o > 0; o >>= 1) sum += __shfl_xor_sync(0xffffffffu, sum, o);
                if (lane == 0) {
                    sum = bf_round(sum);
                    g_gate[blockIdx.x * 16 + min(w - 1 + rr * 3, 15)] = bf_round(1.f / (1.f + __expf(-sum)));
                }
            }
        }
    }
    __syncthreads();
    if (tid == 384) {
        for (int g = 1; g < 8; g++) {
            mbar_expect_tx(sb + BAR_KV + g * 8, 16384);
            bulk_g2s(sb + g * CHUNK_BYTES, kv_src + g * 16384, 16384, sb + BAR_KV + g * 8);
        }
    }
    __syncwarp();

    {
        uint32_t c3f = 0x3F003F00u;
        asm volatile("" : "+r"(c3f));
        const uint64_t kd0 = make_desc(sb, 4096, 128, 0);
        const uint64_t vd0 = make_desc(sb + 8192, 128, 4096, 0);
        if (split && !helper && wg == 3) {
            *(uint4*)(g_qx + blockIdx.x * 2048 + (tid & 127) * 16) = *(const uint4*)(smem + SM_Q + SPLIT_TILE * 2048 + (tid & 127) * 16);
            asm volatile("bar.sync 4, 128;" ::: "memory");
            if (tid == 480) signal(&g_flag[blockIdx.x]);
            __syncwarp();
        }
        const int nunits = helper ? 8 : 4;
#pragma unroll 1
        for (int t = 0; t < nunits; t++) {
            const int cta = UNIT_CTA(t);
            const bool merge = split && !helper && wg == 3 && t == 3;
            const uint32_t g0 = helper ? NSPLIT : 0, g1 = merge ? NSPLIT : 8;
            uint32_t q[4];
            if (helper) {
                if ((tid & 127) == 0) spin_until(&g_flag[cta], 1);
                asm volatile("bar.sync %0, 128;" ::"r"(wg + 1) : "memory");
            }
            LOAD_Q(t)
            float o[12];
            float s0[32], s1[32];
            uint32_t p[16];
#pragma unroll
            for (int i = 0; i < 12; i++) o[i] = 0.f;
            fence_regs<12>(o);
            {
                uint32_t kvbar = sb + BAR_KV + g0 * 8;
                uint64_t kd = kd0 + g0 * 1280, vd = vd0 + g0 * 1280;
                mbar_wait_u(kvbar, 0);
                kvbar += 8;
                if (t == 0) { ts_min(5); ts_max(21); }
                wg_fence();
                qk_n64(s0, q, kd);
                wg_commit();
                wg_wait<0>();
                fence_regs<32>(s0);
#define HALF_STEP(SC, SN, P, KOFF, VOFF)              \
    exp_half<0>(SC, P, c3f);                         \
    wg_wait<0>();                                    \
    wg_fence();                                      \
    qk_n64(SN, q, kd + (KOFF));                      \
    if (SEPQK) wg_commit();                          \
    pv_n24(o, P, vd + (VOFF));                       \
    pv_n24(o, P + 4, vd + (VOFF) + 16);              \
    wg_commit();                                     \
    exp_half<8>(SC + 16, P + 8, c3f);                \
    wg_fence();                                      \
    pv_n24(o, P + 8, vd + (VOFF) + 32);              \
    pv_n24(o, P + 12, vd + (VOFF) + 48);             \
    wg_commit();                                     \
    wg_wait<1 + SEPQK>();                            \
    fence_regs<32>(SN);
                uint32_t p2[16];
#pragma unroll 1
                for (uint32_t g = g0; g < g1; g++) {
                    if (t == 0 && g < 7) mbar_wait_u(kvbar, 0);
                    kvbar += 8;
                    HALF_STEP(s0, s1, p, 64, 0)
                    HALF_STEP(s1, s0, p2, 128, 64)
                    HALF_STEP(s0, s1, p, 192, 128)
                    HALF_STEP(s1, s0, p2, 1280, 192)
                    kd += 1280;
                    vd += 1280;
                }
                wg_wait<0>();
                fence_regs<12>(o);
            }
            int tid2;
            asm volatile("mov.u32 %0, %%tid.x;" : "=r"(tid2));
            volatile uint32_t* redo = (volatile uint32_t*)(smem + SM_MISC + 16) + (tid2 >> 5) * 8;
            if (helper) {
                if (t > 0 && (tid2 & 127) == 96) signal(&g_flag[128 + UNIT_CTA(t - 1)]);
                __syncwarp();
                float4* pp = g_px + cta * 384 + (tid2 & 127);
                pp[0] = make_float4(o[0], o[1], o[2], o[3]);
                pp[128] = make_float4(o[4], o[5], o[6], o[7]);
                pp[256] = make_float4(o[8], o[9], o[10], o[11]);
                continue;
            }
            if (merge) {
                if ((tid2 & 127) == 0) spin_until(&g_flag[128 + cta], 1);
                asm volatile("bar.sync 4, 128;" ::: "memory");
                const float4* pp = g_px + cta * 384 + (tid2 & 127);
                const float4 a = __ldcg(pp), b = __ldcg(pp + 128), c = __ldcg(pp + 256);
                o[0] += a.x; o[1] += a.y; o[2] += a.z; o[3] += a.w;
                o[4] += b.x; o[5] += b.y; o[6] += b.z; o[7] += b.w;
                o[8] += c.x; o[10] += c.z;
            }
            uint32_t any_unsafe;
            {
                float n0 = bf_lo(q[0]) * bf_lo(q[0]) + bf_hi(q[0]) * bf_hi(q[0]) + bf_lo(q[2]) * bf_lo(q[2]) + bf_hi(q[2]) * bf_hi(q[2]);
                float n1 = bf_lo(q[1]) * bf_lo(q[1]) + bf_hi(q[1]) * bf_hi(q[1]) + bf_lo(q[3]) * bf_lo(q[3]) + bf_hi(q[3]) * bf_hi(q[3]);
                n0 += __shfl_xor_sync(0xffffffffu, n0, 1);
                n1 += __shfl_xor_sync(0xffffffffu, n1, 1);
                n0 += __shfl_xor_sync(0xffffffffu, n0, 2);
                n1 += __shfl_xor_sync(0xffffffffu, n1, 2);
                const float kmax2 = *(volatile float*)(smem + SM_MISC + 4);
                const bool unsafe = !(n0 * kmax2 <= 3600.f) || !(n1 * kmax2 <= 3600.f);
                asm volatile(
                    "{\n.reg .pred p, q;\nsetp.ne.u32 q, %1, 0;\nbar.red.or.pred p, %2, 128, q;\nselp.u32 %0, 1, 0, p;\n}"
                    : "=r"(any_unsafe) : "r"((uint32_t)unsafe), "r"(wg + 1) : "memory");
                if ((tid2 & 31) == 0) redo[t] = any_unsafe;
            }
            store_o(o, cta, TILE_OF(wg, t));
        }
        __syncwarp();
        if (helper) {
            asm volatile("bar.sync %0, 128;" ::"r"(wg + 1) : "memory");
            if ((tid & 127) == 96) signal(&g_flag[128 + UNIT_CTA(7)]);
            __syncwarp();
        }
#pragma unroll 1
        for (int t = 0; t < (helper ? 0 : 4); t++) {
            if (!__any_sync(0xffffffffu, ((volatile uint32_t*)(smem + SM_MISC + 16))[(tid >> 5) * 8 + t])) continue;
            const int cta = UNIT_CTA(t);
            uint32_t q[4];
            LOAD_Q(t)
            float o[12], s0[32];
            uint32_t p[16];
#pragma unroll
            for (int i = 0; i < 12; i++) o[i] = 0.f;
            fence_regs<12>(o);
            attn_tile_slow(q, kd0, vd0, o, s0, p);
            store_o(o, cta, TILE_OF(wg, t));
        }
    }
    if (helper) {
        __syncthreads();
        if (tid == 0) finish();
        return;
    }
    asm volatile("fence.proxy.async.shared::cta;" ::: "memory");
    asm volatile("bar.sync %0, 128;" ::"r"(wg + 1) : "memory");
    if (((tid >> 5) & 3) == 3) {
        asm volatile("bar.arrive 0, 512;" ::: "memory");
        if ((tid & 31) == 0) signal(CTR(2 + mb));
        __syncwarp();
    } else {
        asm volatile("bar.sync 0, 512;" ::: "memory");
    }
    ts_min(6); ts_max(22);

    const int orow0 = mb * 128 + (nb >> 2) * 64, ocol0 = (nb & 3) * 128;
    if (wg == 2) {
        if (tid == 288) {
            for (int i = 0; i < 2 * C_STAGES; i++) {
                const int st = i >> 1, b = i & 1;
                const uint32_t s0 = sb + st * C_STAGE_BYTES + b * 24576;
                mbar_expect_tx(sb + BAR_CF + i * 8, 24576);
                tma_2d(s0 + 8192, &maps.wo[b], ocol0, st * 128, sb + BAR_CF + i * 8);
                tma_2d(s0 + 16384, &maps.wo[b], ocol0 + 64, st * 128, sb + BAR_CF + i * 8);
            }
        }
        if (tid == 256) {
            spin_until(CTR(2 + mb), 32);
            fence_async();
            for (int i = 0; i < 2 * C_STAGES; i++) {
                const int st = i >> 1, b = i & 1;
                tma_2d(sb + st * C_STAGE_BYTES + b * 24576, &maps.o, st * 128, b * SEQ + orow0, sb + BAR_CF + i * 8);
            }
            for (int i = 0; i < 2 * C_STAGES; i++) {
                const int st = i >> 1, b = i & 1;
                const uint32_t s0 = sb + st * C_STAGE_BYTES + b * 24576;
                mbar_wait(sb + BAR_CE + i * 8, 0);
                mbar_expect_tx(sb + BAR_CF + i * 8, 24576);
                tma_2d(s0 + 8192, &maps.wo[b], ocol0, st * 128 + 64, sb + BAR_CF + i * 8);
                tma_2d(s0 + 16384, &maps.wo[b], ocol0 + 64, st * 128 + 64, sb + BAR_CF + i * 8);
                tma_2d(s0, &maps.o, st * 128 + 64, b * SEQ + orow0, sb + BAR_CF + i * 8);
            }
            finish();
        }
    } else if (wg < 2) {
        const int warp = tid >> 5, lane = tid & 31;
        float acc[64];
#pragma unroll
        for (int i = 0; i < 64; i++) acc[i] = 0.f;
        fence_regs<64>(acc);
        const int r = lane >> 2, c = lane & 3;
        const int lrow = (warp & 3) * 16 + r;
        float g0 = 0.f, g1 = 0.f;
#pragma unroll
        for (int kb = 0; kb < 8; kb++) {
            const int st = kb % C_STAGES;
            const uint32_t s0 = sb + st * C_STAGE_BYTES + wg * 24576;
            mbar_wait_u(sb + BAR_CF + (st * 2 + wg) * 8, kb >= C_STAGES ? 1 : 0);
            if (kb == 0) {
                ts_min(8); ts_max(24);
                g0 = __ldcg(g_gate + orow0 + lrow);
                g1 = __ldcg(g_gate + orow0 + lrow + 8);
            }
            const uint64_t ad = make_desc(s0, 16, 1024, 1);
            const uint64_t bd = make_desc(s0 + 8192, 8192, 1024, 1);
            wg_fence();
#pragma unroll
            for (int kk = 0; kk < 4; kk++) mma_n128_ss(acc, ad + kk * 2, bd + kk * 128);
            wg_commit();
            if (kb >= 1 && kb <= C_STAGES) {
                wg_wait<1>();
                if (lane == 0) mbar_arrive(sb + BAR_CE + ((kb - 1) * 2 + wg) * 8);
            }
        }
        wg_wait<0>();
        fence_regs<64>(acc);
        ts_min(9); ts_max(25);
        if (wg) { g0 = bf_round(1.f - g0); g1 = bf_round(1.f - g1); }
        uint32_t t[32];
#pragma unroll
        for (int j = 0; j < 16; j++) {
            t[2 * j] = pack_bf16(g0 * bf_round(acc[4 * j]), g0 * bf_round(acc[4 * j + 1]));
            t[2 * j + 1] = pack_bf16(g1 * bf_round(acc[4 * j + 2]), g1 * bf_round(acc[4 * j + 3]));
        }
        uint32_t* xch = (uint32_t*)(smem + SM_XCH);
        const int lt = tid & 127;
#pragma unroll
        for (int j = 0; j < 16; j++) xch[(wg * 16 + j) * 128 + lt] = wg ? t[j] : t[16 + j];
        asm volatile("bar.sync 1, 256;" ::: "memory");
        unsigned char* ot = smem + wg * 16384;
#pragma unroll
        for (int j = 0; j < 16; j++) {
            const uint32_t mine = wg ? t[16 + j] : t[j];
            const uint32_t other = xch[((wg ^ 1) * 16 + j) * 128 + lt];
            const uint32_t v = pack_bf16(bf_lo(mine) + bf_lo(other), bf_hi(mine) + bf_hi(other));
            *(uint32_t*)(ot + (lrow + (j & 1) * 8) * 144 + (j >> 1) * 16 + c * 4) = v;
        }
        asm volatile("bar.sync %0, 128;" ::"r"(wg + 2) : "memory");
#pragma unroll
        for (int i = 0; i < 4; i++) {
            const int idx = i * 128 + lt, row = idx >> 3, ch = idx & 7;
            const uint4 v = *(const uint4*)(ot + row * 144 + ch * 16);
            *(uint4*)(out + (size_t)(orow0 + row) * DM + ocol0 + wg * 64 + ch * 8) = v;
        }
        ts_min(10); ts_max(26);
    }
}

typedef CUresult (*EncodeFn)(CUtensorMap*, CUtensorMapDataType, cuuint32_t, void*, const cuuint64_t*, const cuuint64_t*, const cuuint32_t*,
                             const cuuint32_t*, CUtensorMapInterleave, CUtensorMapSwizzle, CUtensorMapL2promotion, CUtensorMapFloatOOBfill);

static void encode_2d(EncodeFn fn, CUtensorMap* m, const void* ptr, uint64_t inner, uint64_t outer, uint32_t box_inner, uint32_t box_outer,
                      CUtensorMapSwizzle swz = CU_TENSOR_MAP_SWIZZLE_128B) {
    cuuint64_t dims[2] = {inner, outer};
    cuuint64_t strides[1] = {inner * 2};
    cuuint32_t box[2] = {box_inner, box_outer};
    cuuint32_t es[2] = {1, 1};
    fn(m, CU_TENSOR_MAP_DATA_TYPE_BFLOAT16, 2, (void*)ptr, dims, strides, box, es, CU_TENSOR_MAP_INTERLEAVE_NONE, swz,
       CU_TENSOR_MAP_L2_PROMOTION_L2_256B, CU_TENSOR_MAP_FLOAT_OOB_FILL_NONE);
}

extern "C" void kernel_launch(void* const* d_in, const int* in_sizes, int n_in, void* d_out, int out_size) {
    (void)in_sizes; (void)n_in; (void)out_size;
    static Maps m;
    static const void* cached[11] = {0};
    static bool attr_done = false;
    static int grid = 128;
    bool same = true;
    for (int i = 0; i < 11; i++) same = same && (cached[i] == d_in[i]);
    if (!same || !attr_done) {
        void* fnp = nullptr;
        cudaDriverEntryPointQueryResult qr;
        cudaGetDriverEntryPoint("cuTensorMapEncodeTiled", &fnp, cudaEnableDefault, &qr);
        EncodeFn fn = (EncodeFn)fnp;
        void* po = nullptr;
        cudaGetSymbolAddress(&po, g_O);
        encode_2d(fn, &m.x, d_in[0], DM, SEQ, 64, 128);
        encode_2d(fn, &m.wq[0], d_in[1], DM, DM, 64, 64);
        encode_2d(fn, &m.wq[1], d_in[6], DM, DM, 64, 64);
        encode_2d(fn, &m.wkv[0], d_in[2], 16, DM, 8, 256, CU_TENSOR_MAP_SWIZZLE_NONE);
        encode_2d(fn, &m.wkv[1], d_in[3], 16, DM, 8, 256, CU_TENSOR_MAP_SWIZZLE_NONE);
        encode_2d(fn, &m.wkv[2], d_in[7], 16, DM, 8, 256, CU_TENSOR_MAP_SWIZZLE_NONE);
        encode_2d(fn, &m.wkv[3], d_in[8], 16, DM, 8, 256, CU_TENSOR_MAP_SWIZZLE_NONE);
        encode_2d(fn, &m.o, po, DM, 2 * SEQ, 64, 64);
        encode_2d(fn, &m.wo[0], d_in[4], DM, DM, 64, 64);
        encode_2d(fn, &m.wo[1], d_in[9], DM, DM, 64, 64);
        cudaFuncSetAttribute(fused_kernel, cudaFuncAttributeMaxDynamicSharedMemorySize, SMEM_TOTAL);
        int dev = 0, sms = 0;
        cudaGetDevice(&dev);
        cudaDeviceGetAttribute(&sms, cudaDevAttrMultiProcessorCount, dev);
        grid = sms >= 132 ? 132 : 128;
        for (int i = 0; i < 11; i++) cached[i] = d_in[i];
        attr_done = true;
    }
    cudaLaunchAttribute at[1];
    at[0].id = cudaLaunchAttributeCooperative;
    at[0].val.cooperative = 1;
    cudaLaunchConfig_t cfg = {};
    cfg.stream = cudaStreamPerThread;
    cfg.attrs = at;
    cfg.numAttrs = 1;
    cfg.gridDim = dim3(grid);
    cfg.blockDim = dim3(512);
    cfg.dynamicSmemBytes = SMEM_TOTAL;
    cudaLaunchKernelEx(&cfg, fused_kernel, m, (const bf16*)d_in[0], (const bf16*)d_in[10], (const bf16*)d_in[1], (const bf16*)d_in[6],
                       (const bf16*)d_in[4], (const bf16*)d_in[9], (bf16*)d_out);
}
```

```cpp
#include <cuda_runtime.h>
#include <cuda_bf16.h>
#include <cuda.h>
#include <stdint.h>

typedef __nv_bfloat16 bf16;

#define CTR_PAD 32
#define SEQ 2048
#define DM 512
#define ROWS 65536

__device__ __align__(1024) bf16 g_KV[2 * 4 * SEQ * 8];
__device__ __align__(1024) bf16 g_O[2 * ROWS * 16];
__device__ float g_gate[SEQ];
__device__ __align__(128) unsigned char g_qx[128 * 2048];
__device__ __align__(128) float4 g_px[128 * 3 * 128];
__device__ __align__(16) unsigned int g_flag[256];
#define SPLIT_TILE 15
#define NSPLIT 5
__device__ __align__(16) float g_nrm[512];
__device__ __align__(128) unsigned int g_ctr[19 * CTR_PAD];
#define CTR(i) (g_ctr + (i) * CTR_PAD)

#define ts_min(i)
#define ts_max(i)
__device__ __forceinline__ uint32_t smem_u32(const void* p) { return (uint32_t)__cvta_generic_to_shared(p); }
__device__ __forceinline__ uint64_t make_desc(uint32_t saddr, uint32_t lbo, uint32_t sbo, uint32_t swz) {
    uint64_t d = 0;
    d |= (uint64_t)((saddr & 0x3FFFF) >> 4);
    d |= (uint64_t)((lbo & 0x3FFFF) >> 4) << 16;
    d |= (uint64_t)((sbo & 0x3FFFF) >> 4) << 32;
    d |= (uint64_t)swz << 62;
    return d;
}
__device__ __forceinline__ void wg_fence() { asm volatile("wgmma.fence.sync.aligned;" ::: "memory"); }
__device__ __forceinline__ void wg_commit() { asm volatile("wgmma.commit_group.sync.aligned;" ::: "memory"); }
template <int N> __device__ __forceinline__ void wg_wait() { asm volatile("wgmma.wait_group.sync.aligned %0;" ::"n"(N) : "memory"); }
template <int N> __device__ __forceinline__ void fence_regs(float* d) {
#pragma unroll
    for (int i = 0; i < N; i++) asm volatile("" : "+f"(d[i])::"memory");
}
__device__ __forceinline__ void mbar_init(uint32_t bar, uint32_t cnt) { asm volatile("mbarrier.init.shared::cta.b64 [%0], %1;" ::"r"(bar), "r"(cnt)); }
__device__ __forceinline__ void mbar_expect_tx(uint32_t bar, uint32_t bytes) {
    asm volatile("mbarrier.arrive.expect_tx.shared::cta.b64 _, [%0], %1;" ::"r"(bar), "r"(bytes) : "memory");
}
__device__ __forceinline__ void mbar_arrive(uint32_t bar) { asm volatile("mbarrier.arrive.shared::cta.b64 _, [%0];" ::"r"(bar) : "memory"); }
__device__ __forceinline__ void mbar_wait(uint32_t bar, uint32_t parity) {
    asm volatile(
        "{\n.reg .pred p;\n"
        "WAIT_LOOP:\n"
        "mbarrier.try_wait.parity.shared::cta.b64 p, [%0], %1;\n"
        "@p bra DONE;\n"
        "bra WAIT_LOOP;\n"
        "DONE:\n}" ::"r"(bar), "r"(parity) : "memory");
}
__device__ __forceinline__ void mbar_wait_u(uint32_t bar, uint32_t parity) {
    uint32_t ok;
    do {
        asm volatile(
            "{\n.reg .pred p;\nmbarrier.try_wait.parity.shared::cta.b64 p, [%1], %2;\nselp.u32 %0, 1, 0, p;\n}"
            : "=r"(ok) : "r"(bar), "r"(parity) : "memory");
    } while (!__all_sync(0xffffffffu, ok));
}
__device__ __forceinline__ void bulk_g2s(uint32_t dst, const void* src, uint32_t bytes, uint32_t bar) {
    asm volatile("cp.async.bulk.shared::cluster.global.mbarrier::complete_tx::bytes [%0], [%1], %2, [%3];" ::"r"(dst), "l"(src), "r"(bytes), "r"(bar) : "memory");
}
__device__ __forceinline__ void tma_2d(uint32_t dst, const CUtensorMap* map, int c0, int c1, uint32_t bar) {
    asm volatile("cp.async.bulk.tensor.2d.shared::cluster.global.mbarrier::complete_tx::bytes [%0], [%1, {%3, %4}], [%2];" ::"r"(dst), "l"(map), "r"(bar), "r"(c0), "r"(c1) : "memory");
}
__device__ __forceinline__ void l2_prefetch(const void* p, uint32_t bytes) {
    asm volatile("cp.async.bulk.prefetch.L2.global [%0], %1;" ::"l"(p), "r"(bytes) : "memory");
}
__device__ __forceinline__ void fence_async() { asm volatile("fence.proxy.async;" ::: "memory"); }
__device__ __forceinline__ uint32_t pack_bf16(float lo, float hi) {
    uint32_t r;
    asm("cvt.rn.bf16x2.f32 %0, %1, %2;" : "=r"(r) : "f"(hi), "f"(lo));
    return r;
}
__device__ __forceinline__ float bf_lo(uint32_t u) { return __uint_as_float(u << 16); }
__device__ __forceinline__ float bf_hi(uint32_t u) { return __uint_as_float(u & 0xFFFF0000u); }
__device__ __forceinline__ float bf_round(float x) { return __bfloat162float(__float2bfloat16_rn(x)); }

#define A8(b) "+f"(d[b + 0]), "+f"(d[b + 1]), "+f"(d[b + 2]), "+f"(d[b + 3]), "+f"(d[b + 4]), "+f"(d[b + 5]), "+f"(d[b + 6]), "+f"(d[b + 7])
#define W8(b) "=f"(d[b + 0]), "=f"(d[b + 1]), "=f"(d[b + 2]), "=f"(d[b + 3]), "=f"(d[b + 4]), "=f"(d[b + 5]), "=f"(d[b + 6]), "=f"(d[b + 7])

__device__ __forceinline__ void mma_n8_ss(float* d, uint64_t ad, uint64_t bd) {
    asm volatile("wgmma.mma_async.sync.aligned.m64n8k16.f32.bf16.bf16 {%0,%1,%2,%3}, %4, %5, 1, 1, 1, 0, 1;"
                 : "+f"(d[0]), "+f"(d[1]), "+f"(d[2]), "+f"(d[3])
                 : "l"(ad), "l"(bd));
}
__device__ __forceinline__ void mma_n128_ss(float* d, uint64_t ad, uint64_t bd) {
    asm volatile(
        "wgmma.mma_async.sync.aligned.m64n128k16.f32.bf16.bf16 "
        "{%0,%1,%2,%3,%4,%5,%6,%7,%8,%9,%10,%11,%12,%13,%14,%15,%16,%17,%18,%19,%20,%21,%22,%23,%24,%25,%26,%27,%28,%29,%30,%31,"
        "%32,%33,%34,%35,%36,%37,%38,%39,%40,%41,%42,%43,%44,%45,%46,%47,%48,%49,%50,%51,%52,%53,%54,%55,%56,%57,%58,%59,%60,%61,%62,%63}, "
        "%64, %65, 1, 1, 1, 0, 1;"
        : A8(0), A8(8), A8(16), A8(24), A8(32), A8(40), A8(48), A8(56)
        : "l"(ad), "l"(bd));
}
__device__ __forceinline__ void qk_n64(float* d, const uint32_t* a, uint64_t bd) {
    asm volatile(
        "wgmma.mma_async.sync.aligned.m64n64k16.f32.bf16.bf16 "
        "{%0,%1,%2,%3,%4,%5,%6,%7,%8,%9,%10,%11,%12,%13,%14,%15,%16,%17,%18,%19,%20,%21,%22,%23,%24,%25,%26,%27,%28,%29,%30,%31}, "
        "{%32,%33,%34,%35}, %36, 0, 1, 1, 0;"
        : W8(0), W8(8), W8(16), W8(24)
        : "r"(a[0]), "r"(a[1]), "r"(a[2]), "r"(a[3]), "l"(bd));
}
__device__ __forceinline__ void pv_n24(float* d, const uint32_t* a, uint64_t bd) {
    asm volatile(
        "wgmma.mma_async.sync.aligned.m64n24k16.f32.bf16.bf16 {%0,%1,%2,%3,%4,%5,%6,%7,%8,%9,%10,%11}, {%12,%13,%14,%15}, %16, 1, 1, 1, 1;"
        : A8(0), "+f"(d[8]), "+f"(d[9]), "+f"(d[10]), "+f"(d[11])
        : "r"(a[0]), "r"(a[1]), "r"(a[2]), "r"(a[3]), "l"(bd));
}

__device__ __forceinline__ float ex2(float x) {
    float e;
    asm("ex2.approx.ftz.f32 %0, %1;" : "=f"(e) : "f"(x));
    return e;
}
__device__ __forceinline__ uint32_t exp_pair_mufu(float x0, float x1) { return pack_bf16(ex2(x0), ex2(x1)); }

#define MAGIC0 (98304.0f + 127.0f - 75.0f / 128.0f)
#define MAGIC1 (98304.0f + 127.0f - 75.0f / 128.0f - 143.5f)
template <int PRM>
__device__ __forceinline__ uint32_t exp_pair_poly(float x0, float x1, uint32_t c3f) {
    float t0 = x0 + MAGIC0;
    float t1 = x1 + (PRM ? MAGIC0 : MAGIC1);
    uint32_t L, y2, E, r;
    if (PRM)
        asm("prmt.b32 %0, %1, %2, 0x5410;" : "=r"(L) : "r"(__float_as_uint(t0)), "r"(__float_as_uint(t1)));
    else
        L = __float_as_uint(t1) * 65536u + __float_as_uint(t0);
    asm("lop3.b32 %0, %1, 0x007F007F, %2, 0xEA;" : "=r"(y2) : "r"(L), "r"(c3f));
    E = L & 0x7F807F80u;
    asm("fma.rn.bf16x2 %0, %1, %2, %3;" : "=r"(r) : "r"(L), "r"(y2), "r"(E));
    return r;
}
#define EXP_MASK 0x2525u
template <int BASE>
__device__ __forceinline__ void exp_half(const float* s, uint32_t* p, uint32_t c3f) {
#pragma unroll
    for (int i = 0; i < 8; i++) {
        if ((EXP_MASK >> (BASE + i)) & 1) p[i] = exp_pair_mufu(s[2 * i], s[2 * i + 1]);
        else p[i] = exp_pair_poly<0>(s[2 * i], s[2 * i + 1], c3f);
    }
}

struct Maps {
    CUtensorMap x;
    CUtensorMap wq[2];
    CUtensorMap wkv[4];
    CUtensorMap o;
    CUtensorMap wo[2];
};
#define SM_X 20480
#define SM_WKV 151552
#define SM_WQ 159744
#define CHUNK_BYTES 20480
#define SM_Q 163840
#define C_STAGES 4
#define C_STAGE_BYTES 49152
#define SM_XCH 196608
#define SM_BAR 225280
#define BAR_X (SM_BAR)
#define BAR_KV (SM_BAR + 64)
#define BAR_CF (SM_BAR + 128)
#define BAR_CE (SM_BAR + 192)
#define BAR_WF (SM_BAR + 256)
#define BAR_WE (SM_BAR + 288)
#define BAR_WKV (SM_BAR + 320)
#define SM_MISC (SM_BAR + 384)
#define SMEM_TOTAL (SM_BAR + 1024 + 1024)

__device__ __forceinline__ void spin_until(const unsigned int* ctr, unsigned int target) {
    unsigned int v;
    for (unsigned int it = 0; it < (1u << 23); it++) {
        asm volatile("ld.acquire.gpu.global.u32 %0, [%1];" : "=r"(v) : "l"(ctr) : "memory");
        if (v >= target) return;
    }
    __trap();
}
__device__ __forceinline__ void signal(unsigned int* ctr) {
    asm volatile("red.release.gpu.global.add.u32 [%0], 1;" ::"l"(ctr) : "memory");
}

__device__ __forceinline__ void attn_tile_slow(const uint32_t* qq, uint64_t kd0, uint64_t vd0, float* o, float* s, uint32_t* p) {
    float m0 = -INFINITY, m1 = -INFINITY;
#pragma unroll 1
    for (int ch = 0; ch < 32; ch++) {
        wg_fence();
        qk_n64(s, qq, kd0 + (uint64_t)((ch >> 2) * 1280 + (ch & 3) * 64));
        wg_commit();
        wg_wait<0>();
        fence_regs<32>(s);
#pragma unroll
        for (int j = 0; j < 8; j++) {
            m0 = fmaxf(m0, fmaxf(s[4 * j], s[4 * j + 1]));
            m1 = fmaxf(m1, fmaxf(s[4 * j + 2], s[4 * j + 3]));
        }
    }
    m0 = fmaxf(m0, __shfl_xor_sync(0xffffffffu, m0, 1));
    m1 = fmaxf(m1, __shfl_xor_sync(0xffffffffu, m1, 1));
    m0 = fmaxf(m0, __shfl_xor_sync(0xffffffffu, m0, 2));
    m1 = fmaxf(m1, __shfl_xor_sync(0xffffffffu, m1, 2));
#pragma unroll 1
    for (int ch = 0; ch < 32; ch++) {
        wg_fence();
        qk_n64(s, qq, kd0 + (uint64_t)((ch >> 2) * 1280 + (ch & 3) * 64));
        wg_commit();
        wg_wait<0>();
        fence_regs<32>(s);
#pragma unroll
        for (int j = 0; j < 8; j++) {
            p[2 * j] = exp_pair_mufu(s[4 * j] - m0, s[4 * j + 1] - m0);
            p[2 * j + 1] = exp_pair_mufu(s[4 * j + 2] - m1, s[4 * j + 3] - m1);
        }
        wg_fence();
#pragma unroll
        for (int j = 0; j < 4; j++) pv_n24(o, p + 4 * j, vd0 + (uint64_t)((ch >> 2) * 1280 + (ch & 3) * 64 + 16 * j));
        wg_commit();
        wg_wait<0>();
        fence_regs<12>(o);
    }
}

#define TILE_OF(w, t) ((w) * 4 + (t))
#define UNIT_CTA(t) (helper ? (((wg * 8 + (t)) >> 2) * 2 + (int)(blockIdx.x & 1)) * 8 + br * 4 + ((t) & 3) : (int)blockIdx.x)
#define LOAD_Q(t)                                                                                                        \
    {                                                                                                                    \
        const unsigned char* qp = (helper ? g_qx + cta * 2048 : smem + SM_Q + TILE_OF(wg, t) * 2048) + ((tid >> 5) & 3) * 512 + (tid & 31) * 8; \
        asm volatile("ld.volatile.v2.u32 {%0, %1}, [%2];" : "=r"(q[0]), "=r"(q[2]) : "l"(qp) : "memory");                \
        asm volatile("ld.volatile.v2.u32 {%0, %1}, [%2];" : "=r"(q[1]), "=r"(q[3]) : "l"(qp + 256) : "memory");          \
    }
__device__ __forceinline__ void finish() {
    __threadfence();
    if (atomicAdd(CTR(18), 1u) == gridDim.x - 1) {
        for (int i = 0; i < 19; i++) *CTR(i) = 0u;
        for (int i = 0; i < 256; i += 4) *(uint4*)(g_flag + i) = make_uint4(0, 0, 0, 0);
    }
}
__device__ __forceinline__ void store_o(const float* o, int cta, int tile) {
    const int mb = cta >> 3, nb = cta & 7, br = nb >> 2;
    int tid2;
    asm volatile("mov.u32 %0, %%tid.x;" : "=r"(tid2));
    const int lane = tid2 & 31;
    const float l0 = __shfl_sync(0xffffffffu, o[8], lane & ~3);
    const float l1 = __shfl_sync(0xffffffffu, o[10], lane & ~3);
    const float i0 = 1.f / l0, i1 = 1.f / l1;
    const uint32_t row = (uint32_t)(br * SEQ + mb * 128 + (tile & 1) * 64 + ((tid2 >> 5) & 3) * 16 + (lane >> 2));
    bf16* op = g_O + row * DM + ((nb & 3) * 8 + (tile >> 1)) * 16 + (lane & 3) * 2;
    *(uint32_t*)(op) = pack_bf16(o[0] * i0, o[1] * i0);
    *(uint32_t*)(op + 8 * DM) = pack_bf16(o[2] * i1, o[3] * i1);
    *(uint32_t*)(op + 8) = pack_bf16(o[4] * i0, o[5] * i0);
    *(uint32_t*)(op + 8 * DM + 8) = pack_bf16(o[6] * i1, o[7] * i1);
}

__global__ void __launch_bounds__(512, 1) fused_kernel(const __grid_constant__ Maps maps, const bf16* __restrict__ x, const bf16* __restrict__ gate_w,
                                                        const bf16* __restrict__ wqa, const bf16* __restrict__ wqb, const bf16* __restrict__ woa,
                                                        const bf16* __restrict__ wob, bf16* __restrict__ out) {
    const bool split = gridDim.x > 128;
    const bool helper = blockIdx.x >= 128;
    extern __shared__ unsigned char smem_raw[];
    const uint32_t sb = (smem_u32(smem_raw) + 1023) & ~1023u;
    unsigned char* smem = smem_raw + (sb - smem_u32(smem_raw));
    const int tid = threadIdx.x;
    const int wg = __shfl_sync(0xffffffffu, tid >> 7, 0);
    const int mb = blockIdx.x >> 3, nb = blockIdx.x & 7;
    const int br = helper ? (int)((blockIdx.x >> 1) & 1) : nb >> 2;
    ts_min(0); ts_max(16);
    if (tid == 384 && !helper) {
        for (int i = 0; i < 8; i++) mbar_init(sb + BAR_X + i * 8, 1);
        mbar_init(sb + BAR_WKV, 1);
        asm volatile("fence.mbarrier_init.release.cluster;" ::: "memory");
        mbar_expect_tx(sb + BAR_WKV, 8192);
        tma_2d(sb + SM_WKV, &maps.wkv[nb >> 1], (nb & 1) * 8, 0, sb + BAR_WKV);
        tma_2d(sb + SM_WKV + 4096, &maps.wkv[nb >> 1], (nb & 1) * 8, 256, sb + BAR_WKV);
        for (int kb = 0; kb < 8; kb++) {
            mbar_expect_tx(sb + BAR_X + kb * 8, 16384);
            tma_2d(sb + SM_X + kb * 16384, &maps.x, kb * 64, mb * 128, sb + BAR_X + kb * 8);
        }
    }
    if (tid == 352) asm volatile("prefetch.tensormap [%0];" ::"l"(&maps.x) : "memory");
    if (tid == 0) {
        for (int i = 0; i < 8; i++) {
            mbar_init(sb + BAR_KV + i * 8, 1);
            mbar_init(sb + BAR_CF + i * 8, 1);
            mbar_init(sb + BAR_CE + i * 8, 4);
        }
        for (int i = 0; i < 4; i++) {
            mbar_init(sb + BAR_WF + i * 8, 1);
            mbar_init(sb + BAR_WE + i * 8, 8);
        }
        asm volatile("fence.mbarrier_init.release.cluster;" ::: "memory");
    }
    if (tid == 416 && !helper) {
        l2_prefetch(wqa + (size_t)blockIdx.x * 2048, 4096);
        l2_prefetch(wqb + (size_t)blockIdx.x * 2048, 4096);
        asm volatile("prefetch.tensormap [%0];" ::"l"(&maps.wq[br]) : "memory");
        asm volatile("prefetch.tensormap [%0];" ::"l"(&maps.o) : "memory");
        asm volatile("prefetch.tensormap [%0];" ::"l"(&maps.wo[0]) : "memory");
        asm volatile("prefetch.tensormap [%0];" ::"l"(&maps.wo[1]) : "memory");
    }
    __syncthreads();

    const unsigned char* kv_src = (const unsigned char*)g_KV + (size_t)br * 131072;
    if (helper) {
#pragma unroll
        for (int i = 0; i < 4; i++) *(uint4*)(smem + (2 * i + (tid >> 8)) * CHUNK_BYTES + 16384 + (tid & 255) * 16) = make_uint4(0x00003F80u, 0, 0, 0);
        asm volatile("fence.proxy.async.shared::cta;" ::: "memory");
    }
    if (helper && wg < 3) {
    } else if (wg < 2) {
        const int warp = tid >> 5, lane = tid & 31;
        float acc[64];
#pragma unroll
        for (int i = 0; i < 64; i++) acc[i] = 0.f;
        fence_regs<64>(acc);
        asm volatile("bar.sync 3, 384;" ::: "memory");
#pragma unroll
        for (int kb = 0; kb < 8; kb++) {
            const int st = kb & 3;
            mbar_wait_u(sb + BAR_WF + st * 8, kb >> 2);
            if (kb == 0) { ts_min(12); ts_max(28); }
            const uint64_t ad = make_desc(sb + SM_X + kb * 16384 + wg * 8192, 16, 1024, 1);
            const uint64_t bd = make_desc(sb + SM_WQ + st * 16384, 8192, 1024, 1);
            wg_fence();
#pragma unroll
            for (int kk = 0; kk < 4; kk++) mma_n128_ss(acc, ad + kk * 2, bd + kk * 128);
            wg_commit();
            if (kb >= 1 && kb <= 4) {
                wg_wait<1>();
                if (lane == 0) mbar_arrive(sb + BAR_WE + (kb - 1) * 8);
            }
        }
        wg_wait<0>();
        fence_regs<64>(acc);
        ts_min(1); ts_max(17);
        asm volatile("bar.sync 1, 384;" ::: "memory");
        const int r = lane >> 2, c = lane & 3;
        const float qs = 0.25f * 1.4426950408889634f;
        unsigned char* qp = smem + SM_Q + wg * 2048 + ((warp & 3) * 16 + r) * 32 + c * 8;
#pragma unroll
        for (int h = 0; h < 8; h++) {
            const float* a = acc + h * 8;
            *(uint2*)(qp + h * 4096) = make_uint2(pack_bf16(a[0] * qs, a[1] * qs), pack_bf16(a[4] * qs, a[5] * qs));
            *(uint2*)(qp + h * 4096 + 256) = make_uint2(pack_bf16(a[2] * qs, a[3] * qs), pack_bf16(a[6] * qs, a[7] * qs));
        }
        ts_min(2); ts_max(18);
    } else if (wg == 2) {
        const int warp = (tid >> 5) & 3, lane = tid & 31;
        float a0[4] = {0.f, 0.f, 0.f, 0.f}, a1[4] = {0.f, 0.f, 0.f, 0.f};
        fence_regs<4>(a0);
        fence_regs<4>(a1);
        *(uint4*)(smem + 16384 + (tid & 127) * 16) = make_uint4(0x00003F80u, 0, 0, 0);
        *(uint4*)(smem + 18432 + (tid & 127) * 16) = make_uint4(0x00003F80u, 0, 0, 0);
        mbar_wait_u(sb + BAR_WKV, 0);
#pragma unroll
        for (int kb = 0; kb < 8; kb++) {
            mbar_wait_u(sb + BAR_X + kb * 8, 0);
            const uint64_t ad = make_desc(sb + SM_X + kb * 16384, 16, 1024, 1);
            const uint64_t bd = make_desc(sb + SM_WKV + kb * 1024, 128, 128, 0);
            wg_fence();
#pragma unroll
            for (int kk = 0; kk < 4; kk++) {
                mma_n8_ss(a0, ad + kk * 2, bd + kk * 16);
                mma_n8_ss(a1, ad + 512 + kk * 2, bd + kk * 16);
            }
            wg_commit();
        }
        wg_wait<0>();
        fence_regs<4>(a0);
        fence_regs<4>(a1);
        asm volatile("bar.arrive 3, 384;" ::: "memory");
        ts_min(14); ts_max(30);
        const int r = lane >> 2, c = lane & 3;
        const int row = mb * 128 + warp * 16 + r;
        const uint32_t k0 = pack_bf16(a0[0], a0[1]), k1 = pack_bf16(a0[2], a0[3]);
        const uint32_t k2 = pack_bf16(a1[0], a1[1]), k3 = pack_bf16(a1[2], a1[3]);
        bf16* kvp = g_KV + (size_t)br * 65536 + (row >> 8) * 8192 + (nb & 3) * 2048 + (row & 255) * 8 + 2 * c;
        *(uint32_t*)kvp = k0;
        *(uint32_t*)(kvp + 64) = k1;
        *(uint32_t*)(kvp + 512) = k2;
        *(uint32_t*)(kvp + 576) = k3;
        unsigned int mu;
        if (((nb >> 1) & 1) == 0) {
            float n0 = bf_lo(k0) * bf_lo(k0) + bf_hi(k0) * bf_hi(k0);
            float n1 = bf_lo(k1) * bf_lo(k1) + bf_hi(k1) * bf_hi(k1);
            float n2 = bf_lo(k2) * bf_lo(k2) + bf_hi(k2) * bf_hi(k2);
            float n3 = bf_lo(k3) * bf_lo(k3) + bf_hi(k3) * bf_hi(k3);
#pragma unroll
            for (int sft = 1; sft <= 2; sft <<= 1) {
                n0 += __shfl_xor_sync(0xffffffffu, n0, sft);
                n1 += __shfl_xor_sync(0xffffffffu, n1, sft);
                n2 += __shfl_xor_sync(0xffffffffu, n2, sft);
                n3 += __shfl_xor_sync(0xffffffffu, n3, sft);
            }
            mu = max(max(__float_as_uint(n0), __float_as_uint(n1)), max(__float_as_uint(n2), __float_as_uint(n3)));
        } else {
            mu = max(max(max((k0 << 16) & 0x7FFFFFFFu, k0 & 0x7FFF0000u), max((k1 << 16) & 0x7FFFFFFFu, k1 & 0x7FFF0000u)),
                     max(max((k2 << 16) & 0x7FFFFFFFu, k2 & 0x7FFF0000u), max((k3 << 16) & 0x7FFFFFFFu, k3 & 0x7FFF0000u)));
        }
        mu = __reduce_max_sync(0xffffffffu, mu);
        __syncwarp();
        if (lane == 0) {
            g_nrm[(nb * 16 + mb) * 4 + warp] = __uint_as_float(mu);
            signal(CTR(br));
            ts_min(13); ts_max(29);
        }
        asm volatile("bar.sync 1, 384;" ::: "memory");
#pragma unroll
        for (int i = 1; i < 8; i++) {
            *(uint4*)(smem + i * CHUNK_BYTES + 16384 + (tid & 127) * 16) = make_uint4(0x00003F80u, 0, 0, 0);
            *(uint4*)(smem + i * CHUNK_BYTES + 18432 + (tid & 127) * 16) = make_uint4(0x00003F80u, 0, 0, 0);
        }
        asm volatile("fence.proxy.async.shared::cta;" ::: "memory");
    } else {
        const int lane = tid & 31, w = (tid >> 5) & 3;
        if (w == 0) {
            if (lane == 0) {
                if (!helper) {
                mbar_wait(sb + BAR_X + 56, 0);
                ts_min(11); ts_max(27);
                for (int st = 0; st < 4; st++) {
                    mbar_expect_tx(sb + BAR_WF + st * 8, 16384);
                    tma_2d(sb + SM_WQ + st * 16384, &maps.wq[br], (nb & 3) * 128, st * 64, sb + BAR_WF + st * 8);
                    tma_2d(sb + SM_WQ + st * 16384 + 8192, &maps.wq[br], (nb & 3) * 128 + 64, st * 64, sb + BAR_WF + st * 8);
                }
                for (int st = 0; st < 4; st++) {
                    mbar_wait(sb + BAR_WE + st * 8, 0);
                    mbar_expect_tx(sb + BAR_WF + st * 8, 16384);
                    tma_2d(sb + SM_WQ + st * 16384, &maps.wq[br], (nb & 3) * 128, (st + 4) * 64, sb + BAR_WF + st * 8);
                    tma_2d(sb + SM_WQ + st * 16384 + 8192, &maps.wq[br], (nb & 3) * 128 + 64, (st + 4) * 64, sb + BAR_WF + st * 8);
                }
                l2_prefetch(woa + (size_t)blockIdx.x * 2048, 4096);
                l2_prefetch(wob + (size_t)blockIdx.x * 2048, 4096);
                }
                spin_until(CTR(br), 256);
                fence_async();
                ts_min(4); ts_max(20);
                mbar_expect_tx(sb + BAR_KV, 16384);
                bulk_g2s(sb, kv_src, 16384, sb + BAR_KV);
            }
            __syncwarp();
            const uint4 hk = __ldcg((const uint4*)g_nrm + br * 64 + lane);
            const uint4 hv = __ldcg((const uint4*)g_nrm + br * 64 + 32 + lane);
            unsigned int h = max(max(hk.x, hk.y), max(hk.z, hk.w));
            const unsigned int nv = max(max(hv.x, hv.y), max(hv.z, hv.w));
#pragma unroll
            for (int sft = 8; sft > 0; sft >>= 1) h = max(h, __shfl_xor_sync(0xffffffffu, h, sft));
            float kmax2 = __uint_as_float(h) + __uint_as_float(__shfl_xor_sync(0xffffffffu, h, 16));
            const float vmax = __uint_as_float(__reduce_max_sync(0xffffffffu, nv));
            if (!(vmax <= 1.0e15f)) kmax2 = __uint_as_float(0x7FC00000u);
            if (lane == 0) *(volatile float*)(smem + SM_MISC + 4) = kmax2;
        } else if (!helper) {
            const uint4* gw = (const uint4*)(gate_w + lane * 16);
            const uint4 w0 = __ldg(gw), w1 = __ldg(gw + 1);
            const uint32_t wv[8] = {w0.x, w0.y, w0.z, w0.w, w1.x, w1.y, w1.z, w1.w};
            uint4 xa[6][2];
#pragma unroll
            for (int rr = 0; rr < 6; rr++) {
                const int lr = min(w - 1 + rr * 3, 15);
                const uint4* xp = (const uint4*)(x + (size_t)(blockIdx.x * 16 + lr) * DM + lane * 16);
                xa[rr][0] = __ldg(xp);
                xa[rr][1] = __ldg(xp + 1);
            }
#pragma unroll
            for (int rr = 0; rr < 6; rr++) {
                const uint32_t xv[8] = {xa[rr][0].x, xa[rr][0].y, xa[rr][0].z, xa[rr][0].w, xa[rr][1].x, xa[rr][1].y, xa[rr][1].z, xa[rr][1].w};
                float sum = 0.f;
#pragma unroll
                for (int i = 0; i < 8; i++) {
                    sum += bf_round(bf_lo(xv[i]) * bf_lo(wv[i]));
                    sum += bf_round(bf_hi(xv[i]) * bf_hi(wv[i]));
                }
#pragma unroll
                for (int o = 16; o > 0; o >>= 1) sum += __shfl_xor_sync(0xffffffffu, sum, o);
                if (lane == 0) {
                    sum = bf_round(sum);
                    g_gate[blockIdx.x * 16 + min(w - 1 + rr * 3, 15)] = bf_round(1.f / (1.f + __expf(-sum)));
                }
            }
        }
    }
    __syncthreads();
    if (tid == 384) {
        for (int g = 1; g < 8; g++) {
            mbar_expect_tx(sb + BAR_KV + g * 8, 16384);
            bulk_g2s(sb + g * CHUNK_BYTES, kv_src + g * 16384, 16384, sb + BAR_KV + g * 8);
        }
    }
    __syncwarp();

    {
        uint32_t c3f = 0x3F003F00u;
        asm volatile("" : "+r"(c3f));
        const uint64_t kd0 = make_desc(sb, 4096, 128, 0);
        const uint64_t vd0 = make_desc(sb + 8192, 128, 4096, 0);
        if (split && !helper && wg == 3) {
            *(uint4*)(g_qx + blockIdx.x * 2048 + (tid & 127) * 16) = *(const uint4*)(smem + SM_Q + SPLIT_TILE * 2048 + (tid & 127) * 16);
            asm volatile("bar.sync 4, 128;" ::: "memory");
            if (tid == 480) signal(&g_flag[blockIdx.x]);
            __syncwarp();
        }
        const int nunits = helper ? 8 : 4;
#pragma unroll 1
        for (int t = 0; t < nunits; t++) {
            const int cta = UNIT_CTA(t);
            const bool merge = split && !helper && wg == 3 && t == 3;
            const uint32_t g0 = helper ? NSPLIT : 0, g1 = merge ? NSPLIT : 8;
            uint32_t q[4];
            if (helper) {
                if ((tid & 127) == 0) spin_until(&g_flag[cta], 1);
                asm volatile("bar.sync %0, 128;" ::"r"(wg + 1) : "memory");
            }
            LOAD_Q(t)
            float o[12];
            float s0[32], s1[32];
            uint32_t p[16];
#pragma unroll
            for (int i = 0; i < 12; i++) o[i] = 0.f;
            fence_regs<12>(o);
            {
                uint32_t kvbar = sb + BAR_KV + g0 * 8;
                uint64_t kd = kd0 + g0 * 1280, vd = vd0 + g0 * 1280;
                mbar_wait_u(kvbar, 0);
                kvbar += 8;
                if (t == 0) { ts_min(5); ts_max(21); }
                wg_fence();
                qk_n64(s0, q, kd);
                wg_commit();
                wg_wait<0>();
                fence_regs<32>(s0);
#define HALF_STEP(SC, SN, P, KOFF, VOFF)              \
    exp_half<0>(SC, P, c3f);                         \
    wg_wait<0>();                                    \
    wg_fence();                                      \
    qk_n64(SN, q, kd + (KOFF));                      \
    wg_commit();                                     \
    pv_n24(o, P, vd + (VOFF));                       \
    pv_n24(o, P + 4, vd + (VOFF) + 16);              \
    wg_commit();                                     \
    exp_half<8>(SC + 16, P + 8, c3f);                \
    wg_fence();                                      \
    pv_n24(o, P + 8, vd + (VOFF) + 32);              \
    pv_n24(o, P + 12, vd + (VOFF) + 48);             \
    wg_commit();                                     \
    wg_wait<2>();                                    \
    fence_regs<32>(SN);
                uint32_t p2[16];
#pragma unroll 1
                for (uint32_t g = g0; g < g1; g++) {
                    if (t == 0 && g < 7) mbar_wait_u(kvbar, 0);
                    kvbar += 8;
                    HALF_STEP(s0, s1, p, 64, 0)
                    HALF_STEP(s1, s0, p2, 128, 64)
                    HALF_STEP(s0, s1, p, 192, 128)
                    HALF_STEP(s1, s0, p2, 1280, 192)
                    kd += 1280;
                    vd += 1280;
                }
                wg_wait<0>();
                fence_regs<12>(o);
            }
            int tid2;
            asm volatile("mov.u32 %0, %%tid.x;" : "=r"(tid2));
            volatile uint32_t* redo = (volatile uint32_t*)(smem + SM_MISC + 16) + (tid2 >> 5) * 8;
            if (helper) {
                if (t > 0 && (tid2 & 127) == 96) signal(&g_flag[128 + UNIT_CTA(t - 1)]);
                __syncwarp();
                float4* pp = g_px + cta * 384 + (tid2 & 127);
                pp[0] = make_float4(o[0], o[1], o[2], o[3]);
                pp[128] = make_float4(o[4], o[5], o[6], o[7]);
                pp[256] = make_float4(o[8], o[9], o[10], o[11]);
                continue;
            }
            if (merge) {
                if ((tid2 & 127) == 0) spin_until(&g_flag[128 + cta], 1);
                asm volatile("bar.sync 4, 128;" ::: "memory");
                const float4* pp = g_px + cta * 384 + (tid2 & 127);
                const float4 a = __ldcg(pp), b = __ldcg(pp + 128), c = __ldcg(pp + 256);
                o[0] += a.x; o[1] += a.y; o[2] += a.z; o[3] += a.w;
                o[4] += b.x; o[5] += b.y; o[6] += b.z; o[7] += b.w;
                o[8] += c.x; o[10] += c.z;
            }
            uint32_t any_unsafe;
            {
                float n0 = bf_lo(q[0]) * bf_lo(q[0]) + bf_hi(q[0]) * bf_hi(q[0]) + bf_lo(q[2]) * bf_lo(q[2]) + bf_hi(q[2]) * bf_hi(q[2]);
                float n1 = bf_lo(q[1]) * bf_lo(q[1]) + bf_hi(q[1]) * bf_hi(q[1]) + bf_lo(q[3]) * bf_lo(q[3]) + bf_hi(q[3]) * bf_hi(q[3]);
                n0 += __shfl_xor_sync(0xffffffffu, n0, 1);
                n1 += __shfl_xor_sync(0xffffffffu, n1, 1);
                n0 += __shfl_xor_sync(0xffffffffu, n0, 2);
                n1 += __shfl_xor_sync(0xffffffffu, n1, 2);
                const float kmax2 = *(volatile float*)(smem + SM_MISC + 4);
                const bool unsafe = !(n0 * kmax2 <= 3600.f) || !(n1 * kmax2 <= 3600.f);
                asm volatile(
                    "{\n.reg .pred p, q;\nsetp.ne.u32 q, %1, 0;\nbar.red.or.pred p, %2, 128, q;\nselp.u32 %0, 1, 0, p;\n}"
                    : "=r"(any_unsafe) : "r"((uint32_t)unsafe), "r"(wg + 1) : "memory");
                if ((tid2 & 31) == 0) redo[t] = any_unsafe;
            }
            store_o(o, cta, TILE_OF(wg, t));
        }
        __syncwarp();
        if (helper) {
            asm volatile("bar.sync %0, 128;" ::"r"(wg + 1) : "memory");
            if ((tid & 127) == 96) signal(&g_flag[128 + UNIT_CTA(7)]);
            __syncwarp();
        }
#pragma unroll 1
        for (int t = 0; t < (helper ? 0 : 4); t++) {
            if (!__any_sync(0xffffffffu, ((volatile uint32_t*)(smem + SM_MISC + 16))[(tid >> 5) * 8 + t])) continue;
            const int cta = UNIT_CTA(t);
            uint32_t q[4];
            LOAD_Q(t)
            float o[12], s0[32];
            uint32_t p[16];
#pragma unroll
            for (int i = 0; i < 12; i++) o[i] = 0.f;
            fence_regs<12>(o);
            attn_tile_slow(q, kd0, vd0, o, s0, p);
            store_o(o, cta, TILE_OF(wg, t));
        }
    }
    if (helper) {
        __syncthreads();
        if (tid == 0) finish();
        return;
    }
    asm volatile("fence.proxy.async.shared::cta;" ::: "memory");
    asm volatile("bar.sync %0, 128;" ::"r"(wg + 1) : "memory");
    if (((tid >> 5) & 3) == 3) {
        asm volatile("bar.arrive 0, 512;" ::: "memory");
        if ((tid & 31) == 0) signal(CTR(2 + mb));
        __syncwarp();
    } else {
        asm volatile("bar.sync 0, 512;" ::: "memory");
    }
    ts_min(6); ts_max(22);

    const int orow0 = mb * 128 + (nb >> 2) * 64, ocol0 = (nb & 3) * 128;
    if (wg == 2) {
        if (tid == 288) {
            for (int i = 0; i < 2 * C_STAGES; i++) {
                const int st = i >> 1, b = i & 1;
                const uint32_t s0 = sb + st * C_STAGE_BYTES + b * 24576;
                mbar_expect_tx(sb + BAR_CF + i * 8, 24576);
                tma_2d(s0 + 8192, &maps.wo[b], ocol0, st * 128, sb + BAR_CF + i * 8);
                tma_2d(s0 + 16384, &maps.wo[b], ocol0 + 64, st * 128, sb + BAR_CF + i * 8);
            }
        }
        if (tid == 256) {
            spin_until(CTR(2 + mb), 32);
            fence_async();
            for (int i = 0; i < 2 * C_STAGES; i++) {
                const int st = i >> 1, b = i & 1;
                tma_2d(sb + st * C_STAGE_BYTES + b * 24576, &maps.o, st * 128, b * SEQ + orow0, sb + BAR_CF + i * 8);
            }
            for (int i = 0; i < 2 * C_STAGES; i++) {
                const int st = i >> 1, b = i & 1;
                const uint32_t s0 = sb + st * C_STAGE_BYTES + b * 24576;
                mbar_wait(sb + BAR_CE + i * 8, 0);
                mbar_expect_tx(sb + BAR_CF + i * 8, 24576);
                tma_2d(s0 + 8192, &maps.wo[b], ocol0, st * 128 + 64, sb + BAR_CF + i * 8);
                tma_2d(s0 + 16384, &maps.wo[b], ocol0 + 64, st * 128 + 64, sb + BAR_CF + i * 8);
                tma_2d(s0, &maps.o, st * 128 + 64, b * SEQ + orow0, sb + BAR_CF + i * 8);
            }
            finish();
        }
    } else if (wg < 2) {
        const int warp = tid >> 5, lane = tid & 31;
        float acc[64];
#pragma unroll
        for (int i = 0; i < 64; i++) acc[i] = 0.f;
        fence_regs<64>(acc);
        const int r = lane >> 2, c = lane & 3;
        const int lrow = (warp & 3) * 16 + r;
        float g0 = 0.f, g1 = 0.f;
#pragma unroll
        for (int kb = 0; kb < 8; kb++) {
            const int st = kb % C_STAGES;
            const uint32_t s0 = sb + st * C_STAGE_BYTES + wg * 24576;
            mbar_wait_u(sb + BAR_CF + (st * 2 + wg) * 8, kb >= C_STAGES ? 1 : 0);
            if (kb == 0) {
                ts_min(8); ts_max(24);
                g0 = __ldcg(g_gate + orow0 + lrow);
                g1 = __ldcg(g_gate + orow0 + lrow + 8);
            }
            const uint64_t ad = make_desc(s0, 16, 1024, 1);
            const uint64_t bd = make_desc(s0 + 8192, 8192, 1024, 1);
            wg_fence();
#pragma unroll
            for (int kk = 0; kk < 4; kk++) mma_n128_ss(acc, ad + kk * 2, bd + kk * 128);
            wg_commit();
            if (kb >= 1 && kb <= C_STAGES) {
                wg_wait<1>();
                if (lane == 0) mbar_arrive(sb + BAR_CE + ((kb - 1) * 2 + wg) * 8);
            }
        }
        wg_wait<0>();
        fence_regs<64>(acc);
        ts_min(9); ts_max(25);
        if (wg) { g0 = bf_round(1.f - g0); g1 = bf_round(1.f - g1); }
        uint32_t t[32];
#pragma unroll
        for (int j = 0; j < 16; j++) {
            t[2 * j] = pack_bf16(g0 * bf_round(acc[4 * j]), g0 * bf_round(acc[4 * j + 1]));
            t[2 * j + 1] = pack_bf16(g1 * bf_round(acc[4 * j + 2]), g1 * bf_round(acc[4 * j + 3]));
        }
        uint32_t* xch = (uint32_t*)(smem + SM_XCH);
        const int lt = tid & 127;
#pragma unroll
        for (int j = 0; j < 16; j++) xch[(wg * 16 + j) * 128 + lt] = wg ? t[j] : t[16 + j];
        asm volatile("bar.sync 1, 256;" ::: "memory");
        unsigned char* ot = smem + wg * 16384;
#pragma unroll
        for (int j = 0; j < 16; j++) {
            const uint32_t mine = wg ? t[16 + j] : t[j];
            const uint32_t other = xch[((wg ^ 1) * 16 + j) * 128 + lt];
            const uint32_t v = pack_bf16(bf_lo(mine) + bf_lo(other), bf_hi(mine) + bf_hi(other));
            *(uint32_t*)(ot + (lrow + (j & 1) * 8) * 144 + (j >> 1) * 16 + c * 4) = v;
        }
        asm volatile("bar.sync %0, 128;" ::"r"(wg + 2) : "memory");
#pragma unroll
        for (int i = 0; i < 4; i++) {
            const int idx = i * 128 + lt, row = idx >> 3, ch = idx & 7;
            const uint4 v = *(const uint4*)(ot + row * 144 + ch * 16);
            *(uint4*)(out + (size_t)(orow0 + row) * DM + ocol0 + wg * 64 + ch * 8) = v;
        }
        ts_min(10); ts_max(26);
    }
}

typedef CUresult (*EncodeFn)(CUtensorMap*, CUtensorMapDataType, cuuint32_t, void*, const cuuint64_t*, const cuuint64_t*, const cuuint32_t*,
                             const cuuint32_t*, CUtensorMapInterleave, CUtensorMapSwizzle, CUtensorMapL2promotion, CUtensorMapFloatOOBfill);

static void encode_2d(EncodeFn fn, CUtensorMap* m, const void* ptr, uint64_t inner, uint64_t outer, uint32_t box_inner, uint32_t box_outer,
                      CUtensorMapSwizzle swz = CU_TENSOR_MAP_SWIZZLE_128B) {
    cuuint64_t dims[2] = {inner, outer};
    cuuint64_t strides[1] = {inner * 2};
    cuuint32_t box[2] = {box_inner, box_outer};
    cuuint32_t es[2] = {1, 1};
    fn(m, CU_TENSOR_MAP_DATA_TYPE_BFLOAT16, 2, (void*)ptr, dims, strides, box, es, CU_TENSOR_MAP_INTERLEAVE_NONE, swz,
       CU_TENSOR_MAP_L2_PROMOTION_L2_256B, CU_TENSOR_MAP_FLOAT_OOB_FILL_NONE);
}

extern "C" void kernel_launch(void* const* d_in, const int* in_sizes, int n_in, void* d_out, int out_size) {
    (void)in_sizes; (void)n_in; (void)out_size;
    static Maps m;
    static const void* cached[11] = {0};
    static bool attr_done = false;
    static int grid = 128;
    bool same = true;
    for (int i = 0; i < 11; i++) same = same && (cached[i] == d_in[i]);
    if (!same || !attr_done) {
        void* fnp = nullptr;
        cudaDriverEntryPointQueryResult qr;
        cudaGetDriverEntryPoint("cuTensorMapEncodeTiled", &fnp, cudaEnableDefault, &qr);
        EncodeFn fn = (EncodeFn)fnp;
        void* po = nullptr;
        cudaGetSymbolAddress(&po, g_O);
        encode_2d(fn, &m.x, d_in[0], DM, SEQ, 64, 128);
        encode_2d(fn, &m.wq[0], d_in[1], DM, DM, 64, 64);
        encode_2d(fn, &m.wq[1], d_in[6], DM, DM, 64, 64);
        encode_2d(fn, &m.wkv[0], d_in[2], 16, DM, 8, 256, CU_TENSOR_MAP_SWIZZLE_NONE);
        encode_2d(fn, &m.wkv[1], d_in[3], 16, DM, 8, 256, CU_TENSOR_MAP_SWIZZLE_NONE);
        encode_2d(fn, &m.wkv[2], d_in[7], 16, DM, 8, 256, CU_TENSOR_MAP_SWIZZLE_NONE);
        encode_2d(fn, &m.wkv[3], d_in[8], 16, DM, 8, 256, CU_TENSOR_MAP_SWIZZLE_NONE);
        encode_2d(fn, &m.o, po, DM, 2 * SEQ, 64, 64);
        encode_2d(fn, &m.wo[0], d_in[4], DM, DM, 64, 64);
        encode_2d(fn, &m.wo[1], d_in[9], DM, DM, 64, 64);
        cudaFuncSetAttribute(fused_kernel, cudaFuncAttributeMaxDynamicSharedMemorySize, SMEM_TOTAL);
        int dev = 0, sms = 0;
        cudaGetDevice(&dev);
        cudaDeviceGetAttribute(&sms, cudaDevAttrMultiProcessorCount, dev);
        grid = sms >= 132 ? 132 : 128;
        for (int i = 0; i < 11; i++) cached[i] = d_in[i];
        attr_done = true;
    }
    cudaLaunchAttribute at[1];
    at[0].id = cudaLaunchAttributeCooperative;
    at[0].val.cooperative = 1;
    cudaLaunchConfig_t cfg = {};
    cfg.stream = cudaStreamPerThread;
    cfg.attrs = at;
    cfg.numAttrs = 1;
    cfg.gridDim = dim3(grid);
    cfg.blockDim = dim3(512);
    cfg.dynamicSmemBytes = SMEM_TOTAL;
    cudaLaunchKernelEx(&cfg, fused_kernel, m, (const bf16*)d_in[0], (const bf16*)d_in[10], (const bf16*)d_in[1], (const bf16*)d_in[6],
                       (const bf16*)d_in[4], (const bf16*)d_in[9], (bf16*)d_out);
}
```

```cpp
#include <cuda_runtime.h>
#include <cuda_bf16.h>
#include <cuda.h>
#include <stdint.h>

typedef __nv_bfloat16 bf16;

#define CTR_PAD 32
#define SEQ 2048
#define DM 512
#define ROWS 65536

__device__ __align__(1024) bf16 g_KV[2 * 4 * SEQ * 8];
__device__ __align__(1024) bf16 g_O[2 * ROWS * 16];
__device__ float g_gate[SEQ];
__device__ __align__(128) unsigned char g_qx[128 * 2048];
__device__ __align__(128) float4 g_px[128 * 3 * 128];
__device__ __align__(16) unsigned int g_flag[256];
#define SPLIT_TILE 15
#define NSPLIT 5
__device__ __align__(16) float g_nrm[512];
__device__ __align__(128) unsigned int g_ctr[19 * CTR_PAD];
#define CTR(i) (g_ctr + (i) * CTR_PAD)

__device__ __forceinline__ uint32_t smem_u32(const void* p) { return (uint32_t)__cvta_generic_to_shared(p); }
__device__ __forceinline__ uint64_t make_desc(uint32_t saddr, uint32_t lbo, uint32_t sbo, uint32_t swz) {
    uint64_t d = 0;
    d |= (uint64_t)((saddr & 0x3FFFF) >> 4);
    d |= (uint64_t)((lbo & 0x3FFFF) >> 4) << 16;
    d |= (uint64_t)((sbo & 0x3FFFF) >> 4) << 32;
    d |= (uint64_t)swz << 62;
    return d;
}
__device__ __forceinline__ void wg_fence() { asm volatile("wgmma.fence.sync.aligned;" ::: "memory"); }
__device__ __forceinline__ void wg_commit() { asm volatile("wgmma.commit_group.sync.aligned;" ::: "memory"); }
template <int N> __device__ __forceinline__ void wg_wait() { asm volatile("wgmma.wait_group.sync.aligned %0;" ::"n"(N) : "memory"); }
template <int N> __device__ __forceinline__ void fence_regs(float* d) {
#pragma unroll
    for (int i = 0; i < N; i++) asm volatile("" : "+f"(d[i])::"memory");
}
__device__ __forceinline__ void mbar_init(uint32_t bar, uint32_t cnt) { asm volatile("mbarrier.init.shared::cta.b64 [%0], %1;" ::"r"(bar), "r"(cnt)); }
__device__ __forceinline__ void mbar_expect_tx(uint32_t bar, uint32_t bytes) {
    asm volatile("mbarrier.arrive.expect_tx.shared::cta.b64 _, [%0], %1;" ::"r"(bar), "r"(bytes) : "memory");
}
__device__ __forceinline__ void mbar_arrive(uint32_t bar) { asm volatile("mbarrier.arrive.shared::cta.b64 _, [%0];" ::"r"(bar) : "memory"); }
__device__ __forceinline__ void mbar_wait(uint32_t bar, uint32_t parity) {
    asm volatile(
        "{\n.reg .pred p;\n"
        "WAIT_LOOP:\n"
        "mbarrier.try_wait.parity.shared::cta.b64 p, [%0], %1;\n"
        "@p bra DONE;\n"
        "bra WAIT_LOOP;\n"
        "DONE:\n}" ::"r"(bar), "r"(parity) : "memory");
}
__device__ __forceinline__ void mbar_wait_u(uint32_t bar, uint32_t parity) {
    uint32_t ok;
    do {
        asm volatile(
            "{\n.reg .pred p;\nmbarrier.try_wait.parity.shared::cta.b64 p, [%1], %2;\nselp.u32 %0, 1, 0, p;\n}"
            : "=r"(ok) : "r"(bar), "r"(parity) : "memory");
    } while (!__all_sync(0xffffffffu, ok));
}
__device__ __forceinline__ void bulk_g2s(uint32_t dst, const void* src, uint32_t bytes, uint32_t bar) {
    asm volatile("cp.async.bulk.shared::cluster.global.mbarrier::complete_tx::bytes [%0], [%1], %2, [%3];" ::"r"(dst), "l"(src), "r"(bytes), "r"(bar) : "memory");
}
__device__ __forceinline__ void tma_2d(uint32_t dst, const CUtensorMap* map, int c0, int c1, uint32_t bar) {
    asm volatile("cp.async.bulk.tensor.2d.shared::cluster.global.mbarrier::complete_tx::bytes [%0], [%1, {%3, %4}], [%2];" ::"r"(dst), "l"(map), "r"(bar), "r"(c0), "r"(c1) : "memory");
}
__device__ __forceinline__ void l2_prefetch(const void* p, uint32_t bytes) {
    asm volatile("cp.async.bulk.prefetch.L2.global [%0], %1;" ::"l"(p), "r"(bytes) : "memory");
}
__device__ __forceinline__ void fence_async() { asm volatile("fence.proxy.async;" ::: "memory"); }
__device__ __forceinline__ uint32_t pack_bf16(float lo, float hi) {
    uint32_t r;
    asm("cvt.rn.bf16x2.f32 %0, %1, %2;" : "=r"(r) : "f"(hi), "f"(lo));
    return r;
}
__device__ __forceinline__ float bf_lo(uint32_t u) { return __uint_as_float(u << 16); }
__device__ __forceinline__ float bf_hi(uint32_t u) { return __uint_as_float(u & 0xFFFF0000u); }
__device__ __forceinline__ float bf_round(float x) { return __bfloat162float(__float2bfloat16_rn(x)); }

#define A8(b) "+f"(d[b + 0]), "+f"(d[b + 1]), "+f"(d[b + 2]), "+f"(d[b + 3]), "+f"(d[b + 4]), "+f"(d[b + 5]), "+f"(d[b + 6]), "+f"(d[b + 7])
#define W8(b) "=f"(d[b + 0]), "=f"(d[b + 1]), "=f"(d[b + 2]), "=f"(d[b + 3]), "=f"(d[b + 4]), "=f"(d[b + 5]), "=f"(d[b + 6]), "=f"(d[b + 7])

__device__ __forceinline__ void mma_n8_ss(float* d, uint64_t ad, uint64_t bd) {
    asm volatile("wgmma.mma_async.sync.aligned.m64n8k16.f32.bf16.bf16 {%0,%1,%2,%3}, %4, %5, 1, 1, 1, 0, 1;"
                 : "+f"(d[0]), "+f"(d[1]), "+f"(d[2]), "+f"(d[3])
                 : "l"(ad), "l"(bd));
}
__device__ __forceinline__ void mma_n128_ss(float* d, uint64_t ad, uint64_t bd) {
    asm volatile(
        "wgmma.mma_async.sync.aligned.m64n128k16.f32.bf16.bf16 "
        "{%0,%1,%2,%3,%4,%5,%6,%7,%8,%9,%10,%11,%12,%13,%14,%15,%16,%17,%18,%19,%20,%21,%22,%23,%24,%25,%26,%27,%28,%29,%30,%31,"
        "%32,%33,%34,%35,%36,%37,%38,%39,%40,%41,%42,%43,%44,%45,%46,%47,%48,%49,%50,%51,%52,%53,%54,%55,%56,%57,%58,%59,%60,%61,%62,%63}, "
        "%64, %65, 1, 1, 1, 0, 1;"
        : A8(0), A8(8), A8(16), A8(24), A8(32), A8(40), A8(48), A8(56)
        : "l"(ad), "l"(bd));
}
__device__ __forceinline__ void qk_n64(float* d, const uint32_t* a, uint64_t bd) {
    asm volatile(
        "wgmma.mma_async.sync.aligned.m64n64k16.f32.bf16.bf16 "
        "{%0,%1,%2,%3,%4,%5,%6,%7,%8,%9,%10,%11,%12,%13,%14,%15,%16,%17,%18,%19,%20,%21,%22,%23,%24,%25,%26,%27,%28,%29,%30,%31}, "
        "{%32,%33,%34,%35}, %36, 0, 1, 1, 0;"
        : W8(0), W8(8), W8(16), W8(24)
        : "r"(a[0]), "r"(a[1]), "r"(a[2]), "r"(a[3]), "l"(bd));
}
__device__ __forceinline__ void pv_n24(float* d, const uint32_t* a, uint64_t bd) {
    asm volatile(
        "wgmma.mma_async.sync.aligned.m64n24k16.f32.bf16.bf16 {%0,%1,%2,%3,%4,%5,%6,%7,%8,%9,%10,%11}, {%12,%13,%14,%15}, %16, 1, 1, 1, 1;"
        : A8(0), "+f"(d[8]), "+f"(d[9]), "+f"(d[10]), "+f"(d[11])
        : "r"(a[0]), "r"(a[1]), "r"(a[2]), "r"(a[3]), "l"(bd));
}

__device__ __forceinline__ float ex2(float x) {
    float e;
    asm("ex2.approx.ftz.f32 %0, %1;" : "=f"(e) : "f"(x));
    return e;
}
__device__ __forceinline__ uint32_t exp_pair_mufu(float x0, float x1) { return pack_bf16(ex2(x0), ex2(x1)); }

#define MAGIC0 (98304.0f + 127.0f - 75.0f / 128.0f)
#define MAGIC1 (MAGIC0 - 143.5f)
__device__ __forceinline__ uint32_t exp_pair_poly(float x0, float x1, uint32_t c3f) {
    const float t0 = x0 + MAGIC0;
    const float t1 = x1 + MAGIC1;
    const uint32_t L = __float_as_uint(t1) * 65536u + __float_as_uint(t0);
    uint32_t y2, r;
    asm("lop3.b32 %0, %1, 0x007F007F, %2, 0xEA;" : "=r"(y2) : "r"(L), "r"(c3f));
    const uint32_t E = L & 0x7F807F80u;
    asm("fma.rn.bf16x2 %0, %1, %2, %3;" : "=r"(r) : "r"(L), "r"(y2), "r"(E));
    return r;
}
#define EXP_MASK 0x2525u
template <int BASE>
__device__ __forceinline__ void exp_half(const float* s, uint32_t* p, uint32_t c3f) {
#pragma unroll
    for (int i = 0; i < 8; i++) {
        if ((EXP_MASK >> (BASE + i)) & 1) p[i] = exp_pair_mufu(s[2 * i], s[2 * i + 1]);
        else p[i] = exp_pair_poly(s[2 * i], s[2 * i + 1], c3f);
    }
}

struct Maps {
    CUtensorMap x;
    CUtensorMap wq[2];
    CUtensorMap wkv[4];
    CUtensorMap o;
    CUtensorMap wo[2];
};
#define SM_X 20480
#define SM_WKV 151552
#define SM_WQ 159744
#define CHUNK_BYTES 20480
#define SM_Q 163840
#define C_STAGES 4
#define C_STAGE_BYTES 49152
#define SM_XCH 196608
#define SM_BAR 225280
#define BAR_X (SM_BAR)
#define BAR_KV (SM_BAR + 64)
#define BAR_CF (SM_BAR + 128)
#define BAR_CE (SM_BAR + 192)
#define BAR_WF (SM_BAR + 256)
#define BAR_WE (SM_BAR + 288)
#define BAR_WKV (SM_BAR + 320)
#define SM_MISC (SM_BAR + 384)
#define SMEM_TOTAL (SM_BAR + 1024 + 1024)

__device__ __forceinline__ void spin_until(const unsigned int* ctr, unsigned int target) {
    unsigned int v;
    for (unsigned int it = 0; it < (1u << 23); it++) {
        asm volatile("ld.acquire.gpu.global.u32 %0, [%1];" : "=r"(v) : "l"(ctr) : "memory");
        if (v >= target) return;
    }
    __trap();
}
__device__ __forceinline__ void signal(unsigned int* ctr) {
    asm volatile("red.release.gpu.global.add.u32 [%0], 1;" ::"l"(ctr) : "memory");
}

__device__ __forceinline__ void attn_tile_slow(const uint32_t* qq, uint64_t kd0, uint64_t vd0, float* o, float* s, uint32_t* p) {
    float m0 = -INFINITY, m1 = -INFINITY;
#pragma unroll 1
    for (int ch = 0; ch < 32; ch++) {
        wg_fence();
        qk_n64(s, qq, kd0 + (uint64_t)((ch >> 2) * 1280 + (ch & 3) * 64));
        wg_commit();
        wg_wait<0>();
        fence_regs<32>(s);
#pragma unroll
        for (int j = 0; j < 8; j++) {
            m0 = fmaxf(m0, fmaxf(s[4 * j], s[4 * j + 1]));
            m1 = fmaxf(m1, fmaxf(s[4 * j + 2], s[4 * j + 3]));
        }
    }
    m0 = fmaxf(m0, __shfl_xor_sync(0xffffffffu, m0, 1));
    m1 = fmaxf(m1, __shfl_xor_sync(0xffffffffu, m1, 1));
    m0 = fmaxf(m0, __shfl_xor_sync(0xffffffffu, m0, 2));
    m1 = fmaxf(m1, __shfl_xor_sync(0xffffffffu, m1, 2));
#pragma unroll 1
    for (int ch = 0; ch < 32; ch++) {
        wg_fence();
        qk_n64(s, qq, kd0 + (uint64_t)((ch >> 2) * 1280 + (ch & 3) * 64));
        wg_commit();
        wg_wait<0>();
        fence_regs<32>(s);
#pragma unroll
        for (int j = 0; j < 8; j++) {
            p[2 * j] = exp_pair_mufu(s[4 * j] - m0, s[4 * j + 1] - m0);
            p[2 * j + 1] = exp_pair_mufu(s[4 * j + 2] - m1, s[4 * j + 3] - m1);
        }
        wg_fence();
#pragma unroll
        for (int j = 0; j < 4; j++) pv_n24(o, p + 4 * j, vd0 + (uint64_t)((ch >> 2) * 1280 + (ch & 3) * 64 + 16 * j));
        wg_commit();
        wg_wait<0>();
        fence_regs<12>(o);
    }
}

#define TILE_OF(w, t) ((w) * 4 + (t))
#define UNIT_CTA(t) (helper ? (((wg * 8 + (t)) >> 2) * 2 + (int)(blockIdx.x & 1)) * 8 + br * 4 + ((t) & 3) : (int)blockIdx.x)
#define LOAD_Q(t)                                                                                                        \
    {                                                                                                                    \
        const unsigned char* qp = (helper ? g_qx + cta * 2048 : smem + SM_Q + TILE_OF(wg, t) * 2048) + ((tid >> 5) & 3) * 512 + (tid & 31) * 8; \
        asm volatile("ld.volatile.v2.u32 {%0, %1}, [%2];" : "=r"(q[0]), "=r"(q[2]) : "l"(qp) : "memory");                \
        asm volatile("ld.volatile.v2.u32 {%0, %1}, [%2];" : "=r"(q[1]), "=r"(q[3]) : "l"(qp + 256) : "memory");          \
    }
__device__ __forceinline__ void finish() {
    __threadfence();
    if (atomicAdd(CTR(18), 1u) == gridDim.x - 1) {
        for (int i = 0; i < 19; i++) *CTR(i) = 0u;
        for (int i = 0; i < 256; i += 4) *(uint4*)(g_flag + i) = make_uint4(0, 0, 0, 0);
    }
}
__device__ __forceinline__ void store_o(const float* o, int cta, int tile) {
    const int mb = cta >> 3, nb = cta & 7, br = nb >> 2;
    int tid2;
    asm volatile("mov.u32 %0, %%tid.x;" : "=r"(tid2));
    const int lane = tid2 & 31;
    const float l0 = __shfl_sync(0xffffffffu, o[8], lane & ~3);
    const float l1 = __shfl_sync(0xffffffffu, o[10], lane & ~3);
    const float i0 = 1.f / l0, i1 = 1.f / l1;
    const uint32_t row = (uint32_t)(br * SEQ + mb * 128 + (tile & 1) * 64 + ((tid2 >> 5) & 3) * 16 + (lane >> 2));
    bf16* op = g_O + row * DM + ((nb & 3) * 8 + (tile >> 1)) * 16 + (lane & 3) * 2;
    *(uint32_t*)(op) = pack_bf16(o[0] * i0, o[1] * i0);
    *(uint32_t*)(op + 8 * DM) = pack_bf16(o[2] * i1, o[3] * i1);
    *(uint32_t*)(op + 8) = pack_bf16(o[4] * i0, o[5] * i0);
    *(uint32_t*)(op + 8 * DM + 8) = pack_bf16(o[6] * i1, o[7] * i1);
}

__global__ void __launch_bounds__(512, 1) fused_kernel(const __grid_constant__ Maps maps, const bf16* __restrict__ x, const bf16* __restrict__ gate_w,
                                                        const bf16* __restrict__ wqa, const bf16* __restrict__ wqb, const bf16* __restrict__ woa,
                                                        const bf16* __restrict__ wob, bf16* __restrict__ out) {
    const bool split = gridDim.x > 128;
    const bool helper = blockIdx.x >= 128;
    extern __shared__ unsigned char smem_raw[];
    const uint32_t sb = (smem_u32(smem_raw) + 1023) & ~1023u;
    unsigned char* smem = smem_raw + (sb - smem_u32(smem_raw));
    const int tid = threadIdx.x;
    const int wg = __shfl_sync(0xffffffffu, tid >> 7, 0);
    const int mb = blockIdx.x >> 3, nb = blockIdx.x & 7;
    const int br = helper ? (int)((blockIdx.x >> 1) & 1) : nb >> 2;
    if (tid == 384 && !helper) {
        for (int i = 0; i < 8; i++) mbar_init(sb + BAR_X + i * 8, 1);
        mbar_init(sb + BAR_WKV, 1);
        asm volatile("fence.mbarrier_init.release.cluster;" ::: "memory");
        mbar_expect_tx(sb + BAR_WKV, 8192);
        tma_2d(sb + SM_WKV, &maps.wkv[nb >> 1], (nb & 1) * 8, 0, sb + BAR_WKV);
        tma_2d(sb + SM_WKV + 4096, &maps.wkv[nb >> 1], (nb & 1) * 8, 256, sb + BAR_WKV);
        for (int kb = 0; kb < 8; kb++) {
            mbar_expect_tx(sb + BAR_X + kb * 8, 16384);
            tma_2d(sb + SM_X + kb * 16384, &maps.x, kb * 64, mb * 128, sb + BAR_X + kb * 8);
        }
    }
    if (tid == 352) asm volatile("prefetch.tensormap [%0];" ::"l"(&maps.x) : "memory");
    if (tid == 0) {
        for (int i = 0; i < 8; i++) {
            mbar_init(sb + BAR_KV + i * 8, 1);
            mbar_init(sb + BAR_CF + i * 8, 1);
            mbar_init(sb + BAR_CE + i * 8, 4);
        }
        for (int i = 0; i < 4; i++) {
            mbar_init(sb + BAR_WF + i * 8, 1);
            mbar_init(sb + BAR_WE + i * 8, 8);
        }
        asm volatile("fence.mbarrier_init.release.cluster;" ::: "memory");
    }
    if (tid == 416 && !helper) {
        l2_prefetch(wqa + (size_t)blockIdx.x * 2048, 4096);
        l2_prefetch(wqb + (size_t)blockIdx.x * 2048, 4096);
        asm volatile("prefetch.tensormap [%0];" ::"l"(&maps.wq[br]) : "memory");
        asm volatile("prefetch.tensormap [%0];" ::"l"(&maps.o) : "memory");
        asm volatile("prefetch.tensormap [%0];" ::"l"(&maps.wo[0]) : "memory");
        asm volatile("prefetch.tensormap [%0];" ::"l"(&maps.wo[1]) : "memory");
    }
    __syncthreads();

    const unsigned char* kv_src = (const unsigned char*)g_KV + (size_t)br * 131072;
    if (helper) {
#pragma unroll
        for (int i = 0; i < 4; i++) *(uint4*)(smem + (2 * i + (tid >> 8)) * CHUNK_BYTES + 16384 + (tid & 255) * 16) = make_uint4(0x00003F80u, 0, 0, 0);
        asm volatile("fence.proxy.async.shared::cta;" ::: "memory");
    }
    if (helper && wg < 3) {
    } else if (wg < 2) {
        const int warp = tid >> 5, lane = tid & 31;
        float acc[64];
#pragma unroll
        for (int i = 0; i < 64; i++) acc[i] = 0.f;
        fence_regs<64>(acc);
        asm volatile("bar.sync 3, 384;" ::: "memory");
#pragma unroll
        for (int kb = 0; kb < 8; kb++) {
            const int st = kb & 3;
            mbar_wait_u(sb + BAR_WF + st * 8, kb >> 2);
            const uint64_t ad = make_desc(sb + SM_X + kb * 16384 + wg * 8192, 16, 1024, 1);
            const uint64_t bd = make_desc(sb + SM_WQ + st * 16384, 8192, 1024, 1);
            wg_fence();
#pragma unroll
            for (int kk = 0; kk < 4; kk++) mma_n128_ss(acc, ad + kk * 2, bd + kk * 128);
            wg_commit();
            if (kb >= 1 && kb <= 4) {
                wg_wait<1>();
                if (lane == 0) mbar_arrive(sb + BAR_WE + (kb - 1) * 8);
            }
        }
        wg_wait<0>();
        fence_regs<64>(acc);
        asm volatile("bar.sync 1, 384;" ::: "memory");
        const int r = lane >> 2, c = lane & 3;
        const float qs = 0.25f * 1.4426950408889634f;
        unsigned char* qp = smem + SM_Q + wg * 2048 + ((warp & 3) * 16 + r) * 32 + c * 8;
#pragma unroll
        for (int h = 0; h < 8; h++) {
            const float* a = acc + h * 8;
            *(uint2*)(qp + h * 4096) = make_uint2(pack_bf16(a[0] * qs, a[1] * qs), pack_bf16(a[4] * qs, a[5] * qs));
            *(uint2*)(qp + h * 4096 + 256) = make_uint2(pack_bf16(a[2] * qs, a[3] * qs), pack_bf16(a[6] * qs, a[7] * qs));
        }
    } else if (wg == 2) {
        const int warp = (tid >> 5) & 3, lane = tid & 31;
        float a0[4] = {0.f, 0.f, 0.f, 0.f}, a1[4] = {0.f, 0.f, 0.f, 0.f};
        fence_regs<4>(a0);
        fence_regs<4>(a1);
        *(uint4*)(smem + 16384 + (tid & 127) * 16) = make_uint4(0x00003F80u, 0, 0, 0);
        *(uint4*)(smem + 18432 + (tid & 127) * 16) = make_uint4(0x00003F80u, 0, 0, 0);
        mbar_wait_u(sb + BAR_WKV, 0);
#pragma unroll
        for (int kb = 0; kb < 8; kb++) {
            mbar_wait_u(sb + BAR_X + kb * 8, 0);
            const uint64_t ad = make_desc(sb + SM_X + kb * 16384, 16, 1024, 1);
            const uint64_t bd = make_desc(sb + SM_WKV + kb * 1024, 128, 128, 0);
            wg_fence();
#pragma unroll
            for (int kk = 0; kk < 4; kk++) {
                mma_n8_ss(a0, ad + kk * 2, bd + kk * 16);
                mma_n8_ss(a1, ad + 512 + kk * 2, bd + kk * 16);
            }
            wg_commit();
        }
        wg_wait<0>();
        fence_regs<4>(a0);
        fence_regs<4>(a1);
        asm volatile("bar.arrive 3, 384;" ::: "memory");
        const int r = lane >> 2, c = lane & 3;
        const int row = mb * 128 + warp * 16 + r;
        const uint32_t k0 = pack_bf16(a0[0], a0[1]), k1 = pack_bf16(a0[2], a0[3]);
        const uint32_t k2 = pack_bf16(a1[0], a1[1]), k3 = pack_bf16(a1[2], a1[3]);
        bf16* kvp = g_KV + (size_t)br * 65536 + (row >> 8) * 8192 + (nb & 3) * 2048 + (row & 255) * 8 + 2 * c;
        *(uint32_t*)kvp = k0;
        *(uint32_t*)(kvp + 64) = k1;
        *(uint32_t*)(kvp + 512) = k2;
        *(uint32_t*)(kvp + 576) = k3;
        unsigned int mu;
        if (((nb >> 1) & 1) == 0) {
            float n0 = bf_lo(k0) * bf_lo(k0) + bf_hi(k0) * bf_hi(k0);
            float n1 = bf_lo(k1) * bf_lo(k1) + bf_hi(k1) * bf_hi(k1);
            float n2 = bf_lo(k2) * bf_lo(k2) + bf_hi(k2) * bf_hi(k2);
            float n3 = bf_lo(k3) * bf_lo(k3) + bf_hi(k3) * bf_hi(k3);
#pragma unroll
            for (int sft = 1; sft <= 2; sft <<= 1) {
                n0 += __shfl_xor_sync(0xffffffffu, n0, sft);
                n1 += __shfl_xor_sync(0xffffffffu, n1, sft);
                n2 += __shfl_xor_sync(0xffffffffu, n2, sft);
                n3 += __shfl_xor_sync(0xffffffffu, n3, sft);
            }
            mu = max(max(__float_as_uint(n0), __float_as_uint(n1)), max(__float_as_uint(n2), __float_as_uint(n3)));
        } else {
            mu = max(max(max((k0 << 16) & 0x7FFFFFFFu, k0 & 0x7FFF0000u), max((k1 << 16) & 0x7FFFFFFFu, k1 & 0x7FFF0000u)),
                     max(max((k2 << 16) & 0x7FFFFFFFu, k2 & 0x7FFF0000u), max((k3 << 16) & 0x7FFFFFFFu, k3 & 0x7FFF0000u)));
        }
        mu = __reduce_max_sync(0xffffffffu, mu);
        __syncwarp();
        if (lane == 0) {
            g_nrm[(nb * 16 + mb) * 4 + warp] = __uint_as_float(mu);
            signal(CTR(br));
        }
        asm volatile("bar.sync 1, 384;" ::: "memory");
#pragma unroll
        for (int i = 1; i < 8; i++) {
            *(uint4*)(smem + i * CHUNK_BYTES + 16384 + (tid & 127) * 16) = make_uint4(0x00003F80u, 0, 0, 0);
            *(uint4*)(smem + i * CHUNK_BYTES + 18432 + (tid & 127) * 16) = make_uint4(0x00003F80u, 0, 0, 0);
        }
        asm volatile("fence.proxy.async.shared::cta;" ::: "memory");
    } else {
        const int lane = tid & 31, w = (tid >> 5) & 3;
        if (w == 0) {
            if (lane == 0) {
                if (!helper) {
                mbar_wait(sb + BAR_X + 56, 0);
                for (int st = 0; st < 4; st++) {
                    mbar_expect_tx(sb + BAR_WF + st * 8, 16384);
                    tma_2d(sb + SM_WQ + st * 16384, &maps.wq[br], (nb & 3) * 128, st * 64, sb + BAR_WF + st * 8);
                    tma_2d(sb + SM_WQ + st * 16384 + 8192, &maps.wq[br], (nb & 3) * 128 + 64, st * 64, sb + BAR_WF + st * 8);
                }
                for (int st = 0; st < 4; st++) {
                    mbar_wait(sb + BAR_WE + st * 8, 0);
                    mbar_expect_tx(sb + BAR_WF + st * 8, 16384);
                    tma_2d(sb + SM_WQ + st * 16384, &maps.wq[br], (nb & 3) * 128, (st + 4) * 64, sb + BAR_WF + st * 8);
                    tma_2d(sb + SM_WQ + st * 16384 + 8192, &maps.wq[br], (nb & 3) * 128 + 64, (st + 4) * 64, sb + BAR_WF + st * 8);
                }
                l2_prefetch(woa + (size_t)blockIdx.x * 2048, 4096);
                l2_prefetch(wob + (size_t)blockIdx.x * 2048, 4096);
                }
                spin_until(CTR(br), 256);
                fence_async();
                mbar_expect_tx(sb + BAR_KV, 16384);
                bulk_g2s(sb, kv_src, 16384, sb + BAR_KV);
            }
            __syncwarp();
            const uint4 hk = __ldcg((const uint4*)g_nrm + br * 64 + lane);
            const uint4 hv = __ldcg((const uint4*)g_nrm + br * 64 + 32 + lane);
            unsigned int h = max(max(hk.x, hk.y), max(hk.z, hk.w));
            const unsigned int nv = max(max(hv.x, hv.y), max(hv.z, hv.w));
#pragma unroll
            for (int sft = 8; sft > 0; sft >>= 1) h = max(h, __shfl_xor_sync(0xffffffffu, h, sft));
            float kmax2 = __uint_as_float(h) + __uint_as_float(__shfl_xor_sync(0xffffffffu, h, 16));
            const float vmax = __uint_as_float(__reduce_max_sync(0xffffffffu, nv));
            if (!(vmax <= 1.0e15f)) kmax2 = __uint_as_float(0x7FC00000u);
            if (lane == 0) *(volatile float*)(smem + SM_MISC + 4) = kmax2;
        } else if (!helper) {
            const uint4* gw = (const uint4*)(gate_w + lane * 16);
            const uint4 w0 = __ldg(gw), w1 = __ldg(gw + 1);
            const uint32_t wv[8] = {w0.x, w0.y, w0.z, w0.w, w1.x, w1.y, w1.z, w1.w};
            uint4 xa[6][2];
#pragma unroll
            for (int rr = 0; rr < 6; rr++) {
                const int lr = min(w - 1 + rr * 3, 15);
                const uint4* xp = (const uint4*)(x + (size_t)(blockIdx.x * 16 + lr) * DM + lane * 16);
                xa[rr][0] = __ldg(xp);
                xa[rr][1] = __ldg(xp + 1);
            }
#pragma unroll
            for (int rr = 0; rr < 6; rr++) {
                const uint32_t xv[8] = {xa[rr][0].x, xa[rr][0].y, xa[rr][0].z, xa[rr][0].w, xa[rr][1].x, xa[rr][1].y, xa[rr][1].z, xa[rr][1].w};
                float sum = 0.f;
#pragma unroll
                for (int i = 0; i < 8; i++) {
                    sum += bf_round(bf_lo(xv[i]) * bf_lo(wv[i]));
                    sum += bf_round(bf_hi(xv[i]) * bf_hi(wv[i]));
                }
#pragma unroll
                for (int o = 16; o > 0; o >>= 1) sum += __shfl_xor_sync(0xffffffffu, sum, o);
                if (lane == 0) {
                    sum = bf_round(sum);
                    g_gate[blockIdx.x * 16 + min(w - 1 + rr * 3, 15)] = bf_round(1.f / (1.f + __expf(-sum)));
                }
            }
        }
    }
    __syncthreads();
    if (tid == 384) {
        for (int g = 1; g < 8; g++) {
            mbar_expect_tx(sb + BAR_KV + g * 8, 16384);
            bulk_g2s(sb + g * CHUNK_BYTES, kv_src + g * 16384, 16384, sb + BAR_KV + g * 8);
        }
    }
    __syncwarp();

    {
        uint32_t c3f = 0x3F003F00u;
        asm volatile("" : "+r"(c3f));
        const uint64_t kd0 = make_desc(sb, 4096, 128, 0);
        const uint64_t vd0 = make_desc(sb + 8192, 128, 4096, 0);
        if (split && !helper && wg == 3) {
            *(uint4*)(g_qx + blockIdx.x * 2048 + (tid & 127) * 16) = *(const uint4*)(smem + SM_Q + SPLIT_TILE * 2048 + (tid & 127) * 16);
            asm volatile("bar.sync 4, 128;" ::: "memory");
            if (tid == 480) signal(&g_flag[blockIdx.x]);
            __syncwarp();
        }
        const int nunits = helper ? 8 : 4;
#pragma unroll 1
        for (int t = 0; t < nunits; t++) {
            const int cta = UNIT_CTA(t);
            const bool merge = split && !helper && wg == 3 && t == 3;
            const uint32_t g0 = helper ? NSPLIT : 0, g1 = merge ? NSPLIT : 8;
            uint32_t q[4];
            if (helper) {
                if ((tid & 127) == 0) spin_until(&g_flag[cta], 1);
                asm volatile("bar.sync %0, 128;" ::"r"(wg + 1) : "memory");
            }
            LOAD_Q(t)
            float o[12];
            float s0[32], s1[32];
            uint32_t p[16];
#pragma unroll
            for (int i = 0; i < 12; i++) o[i] = 0.f;
            fence_regs<12>(o);
            {
                uint32_t kvbar = sb + BAR_KV + g0 * 8;
                uint64_t kd = kd0 + g0 * 1280, vd = vd0 + g0 * 1280;
                mbar_wait_u(kvbar, 0);
                kvbar += 8;
                wg_fence();
                qk_n64(s0, q, kd);
                wg_commit();
                wg_wait<0>();
                fence_regs<32>(s0);
#define HALF_STEP(SC, SN, P, KOFF, VOFF)              \
    exp_half<0>(SC, P, c3f);                         \
    wg_wait<0>();                                    \
    wg_fence();                                      \
    qk_n64(SN, q, kd + (KOFF));                      \
    wg_commit();                                     \
    pv_n24(o, P, vd + (VOFF));                       \
    pv_n24(o, P + 4, vd + (VOFF) + 16);              \
    wg_commit();                                     \
    exp_half<8>(SC + 16, P + 8, c3f);                \
    wg_fence();                                      \
    pv_n24(o, P + 8, vd + (VOFF) + 32);              \
    pv_n24(o, P + 12, vd + (VOFF) + 48);             \
    wg_commit();                                     \
    wg_wait<2>();                                    \
    fence_regs<32>(SN);
                uint32_t p2[16];
#pragma unroll 1
                for (uint32_t g = g0; g < g1; g++) {
                    if (t == 0 && g < 7) mbar_wait_u(kvbar, 0);
                    kvbar += 8;
                    HALF_STEP(s0, s1, p, 64, 0)
                    HALF_STEP(s1, s0, p2, 128, 64)
                    HALF_STEP(s0, s1, p, 192, 128)
                    HALF_STEP(s1, s0, p2, 1280, 192)
                    kd += 1280;
                    vd += 1280;
                }
                wg_wait<0>();
                fence_regs<12>(o);
            }
            int tid2;
            asm volatile("mov.u32 %0, %%tid.x;" : "=r"(tid2));
            volatile uint32_t* redo = (volatile uint32_t*)(smem + SM_MISC + 16) + (tid2 >> 5) * 8;
            if (helper) {
                if (t > 0 && (tid2 & 127) == 96) signal(&g_flag[128 + UNIT_CTA(t - 1)]);
                __syncwarp();
                float4* pp = g_px + cta * 384 + (tid2 & 127);
                pp[0] = make_float4(o[0], o[1], o[2], o[3]);
                pp[128] = make_float4(o[4], o[5], o[6], o[7]);
                pp[256] = make_float4(o[8], o[9], o[10], o[11]);
                continue;
            }
            if (merge) {
                if ((tid2 & 127) == 0) spin_until(&g_flag[128 + cta], 1);
                asm volatile("bar.sync 4, 128;" ::: "memory");
                const float4* pp = g_px + cta * 384 + (tid2 & 127);
                const float4 a = __ldcg(pp), b = __ldcg(pp + 128), c = __ldcg(pp + 256);
                o[0] += a.x; o[1] += a.y; o[2] += a.z; o[3] += a.w;
                o[4] += b.x; o[5] += b.y; o[6] += b.z; o[7] += b.w;
                o[8] += c.x; o[10] += c.z;
            }
            uint32_t any_unsafe;
            {
                float n0 = bf_lo(q[0]) * bf_lo(q[0]) + bf_hi(q[0]) * bf_hi(q[0]) + bf_lo(q[2]) * bf_lo(q[2]) + bf_hi(q[2]) * bf_hi(q[2]);
                float n1 = bf_lo(q[1]) * bf_lo(q[1]) + bf_hi(q[1]) * bf_hi(q[1]) + bf_lo(q[3]) * bf_lo(q[3]) + bf_hi(q[3]) * bf_hi(q[3]);
                n0 += __shfl_xor_sync(0xffffffffu, n0, 1);
                n1 += __shfl_xor_sync(0xffffffffu, n1, 1);
                n0 += __shfl_xor_sync(0xffffffffu, n0, 2);
                n1 += __shfl_xor_sync(0xffffffffu, n1, 2);
                const float kmax2 = *(volatile float*)(smem + SM_MISC + 4);
                const bool unsafe = !(n0 * kmax2 <= 3600.f) || !(n1 * kmax2 <= 3600.f);
                asm volatile(
                    "{\n.reg .pred p, q;\nsetp.ne.u32 q, %1, 0;\nbar.red.or.pred p, %2, 128, q;\nselp.u32 %0, 1, 0, p;\n}"
                    : "=r"(any_unsafe) : "r"((uint32_t)unsafe), "r"(wg + 1) : "memory");
                if ((tid2 & 31) == 0) redo[t] = any_unsafe;
            }
            store_o(o, cta, TILE_OF(wg, t));
        }
        __syncwarp();
        if (helper) {
            asm volatile("bar.sync %0, 128;" ::"r"(wg + 1) : "memory");
            if ((tid & 127) == 96) signal(&g_flag[128 + UNIT_CTA(7)]);
            __syncwarp();
        }
#pragma unroll 1
        for (int t = 0; t < (helper ? 0 : 4); t++) {
            if (!__any_sync(0xffffffffu, ((volatile uint32_t*)(smem + SM_MISC + 16))[(tid >> 5) * 8 + t])) continue;
            const int cta = UNIT_CTA(t);
            uint32_t q[4];
            LOAD_Q(t)
            float o[12], s0[32];
            uint32_t p[16];
#pragma unroll
            for (int i = 0; i < 12; i++) o[i] = 0.f;
            fence_regs<12>(o);
            attn_tile_slow(q, kd0, vd0, o, s0, p);
            store_o(o, cta, TILE_OF(wg, t));
        }
    }
    if (helper) {
        __syncthreads();
        if (tid == 0) finish();
        return;
    }
    asm volatile("fence.proxy.async.shared::cta;" ::: "memory");
    asm volatile("bar.sync %0, 128;" ::"r"(wg + 1) : "memory");
    if (((tid >> 5) & 3) == 3) {
        asm volatile("bar.arrive 0, 512;" ::: "memory");
        if ((tid & 31) == 0) signal(CTR(2 + mb));
        __syncwarp();
    } else {
        asm volatile("bar.sync 0, 512;" ::: "memory");
    }

    const int orow0 = mb * 128 + (nb >> 2) * 64, ocol0 = (nb & 3) * 128;
    if (wg == 2) {
        if (tid == 288) {
            for (int i = 0; i < 2 * C_STAGES; i++) {
                const int st = i >> 1, b = i & 1;
                const uint32_t s0 = sb + st * C_STAGE_BYTES + b * 24576;
                mbar_expect_tx(sb + BAR_CF + i * 8, 24576);
                tma_2d(s0 + 8192, &maps.wo[b], ocol0, st * 128, sb + BAR_CF + i * 8);
                tma_2d(s0 + 16384, &maps.wo[b], ocol0 + 64, st * 128, sb + BAR_CF + i * 8);
            }
        }
        if (tid == 256) {
            spin_until(CTR(2 + mb), 32);
            fence_async();
            for (int i = 0; i < 2 * C_STAGES; i++) {
                const int st = i >> 1, b = i & 1;
                tma_2d(sb + st * C_STAGE_BYTES + b * 24576, &maps.o, st * 128, b * SEQ + orow0, sb + BAR_CF + i * 8);
            }
            for (int i = 0; i < 2 * C_STAGES; i++) {
                const int st = i >> 1, b = i & 1;
                const uint32_t s0 = sb + st * C_STAGE_BYTES + b * 24576;
                mbar_wait(sb + BAR_CE + i * 8, 0);
                mbar_expect_tx(sb + BAR_CF + i * 8, 24576);
                tma_2d(s0 + 8192, &maps.wo[b], ocol0, st * 128 + 64, sb + BAR_CF + i * 8);
                tma_2d(s0 + 16384, &maps.wo[b], ocol0 + 64, st * 128 + 64, sb + BAR_CF + i * 8);
                tma_2d(s0, &maps.o, st * 128 + 64, b * SEQ + orow0, sb + BAR_CF + i * 8);
            }
            finish();
        }
    } else if (wg < 2) {
        const int warp = tid >> 5, lane = tid & 31;
        float acc[64];
#pragma unroll
        for (int i = 0; i < 64; i++) acc[i] = 0.f;
        fence_regs<64>(acc);
        const int r = lane >> 2, c = lane & 3;
        const int lrow = (warp & 3) * 16 + r;
        float g0 = 0.f, g1 = 0.f;
#pragma unroll
        for (int kb = 0; kb < 8; kb++) {
            const int st = kb % C_STAGES;
            const uint32_t s0 = sb + st * C_STAGE_BYTES + wg * 24576;
            mbar_wait_u(sb + BAR_CF + (st * 2 + wg) * 8, kb >= C_STAGES ? 1 : 0);
            if (kb == 0) {
                g0 = __ldcg(g_gate + orow0 + lrow);
                g1 = __ldcg(g_gate + orow0 + lrow + 8);
            }
            const uint64_t ad = make_desc(s0, 16, 1024, 1);
            const uint64_t bd = make_desc(s0 + 8192, 8192, 1024, 1);
            wg_fence();
#pragma unroll
            for (int kk = 0; kk < 4; kk++) mma_n128_ss(acc, ad + kk * 2, bd + kk * 128);
            wg_commit();
            if (kb >= 1 && kb <= C_STAGES) {
                wg_wait<1>();
                if (lane == 0) mbar_arrive(sb + BAR_CE + ((kb - 1) * 2 + wg) * 8);
            }
        }
        wg_wait<0>();
        fence_regs<64>(acc);
        if (wg) { g0 = bf_round(1.f - g0); g1 = bf_round(1.f - g1); }
        uint32_t t[32];
#pragma unroll
        for (int j = 0; j < 16; j++) {
            t[2 * j] = pack_bf16(g0 * bf_round(acc[4 * j]), g0 * bf_round(acc[4 * j + 1]));
            t[2 * j + 1] = pack_bf16(g1 * bf_round(acc[4 * j + 2]), g1 * bf_round(acc[4 * j + 3]));
        }
        uint32_t* xch = (uint32_t*)(smem + SM_XCH);
        const int lt = tid & 127;
#pragma unroll
        for (int j = 0; j < 16; j++) xch[(wg * 16 + j) * 128 + lt] = wg ? t[j] : t[16 + j];
        asm volatile("bar.sync 1, 256;" ::: "memory");
        unsigned char* ot = smem + wg * 16384;
#pragma unroll
        for (int j = 0; j < 16; j++) {
            const uint32_t mine = wg ? t[16 + j] : t[j];
            const uint32_t other = xch[((wg ^ 1) * 16 + j) * 128 + lt];
            const uint32_t v = pack_bf16(bf_lo(mine) + bf_lo(other), bf_hi(mine) + bf_hi(other));
            *(uint32_t*)(ot + (lrow + (j & 1) * 8) * 144 + (j >> 1) * 16 + c * 4) = v;
        }
        asm volatile("bar.sync %0, 128;" ::"r"(wg + 2) : "memory");
#pragma unroll
        for (int i = 0; i < 4; i++) {
            const int idx = i * 128 + lt, row = idx >> 3, ch = idx & 7;
            const uint4 v = *(const uint4*)(ot + row * 144 + ch * 16);
            *(uint4*)(out + (size_t)(orow0 + row) * DM + ocol0 + wg * 64 + ch * 8) = v;
        }
    }
}

typedef CUresult (*EncodeFn)(CUtensorMap*, CUtensorMapDataType, cuuint32_t, void*, const cuuint64_t*, const cuuint64_t*, const cuuint32_t*,
                             const cuuint32_t*, CUtensorMapInterleave, CUtensorMapSwizzle, CUtensorMapL2promotion, CUtensorMapFloatOOBfill);

static void encode_2d(EncodeFn fn, CUtensorMap* m, const void* ptr, uint64_t inner, uint64_t outer, uint32_t box_inner, uint32_t box_outer,
                      CUtensorMapSwizzle swz = CU_TENSOR_MAP_SWIZZLE_128B) {
    cuuint64_t dims[2] = {inner, outer};
    cuuint64_t strides[1] = {inner * 2};
    cuuint32_t box[2] = {box_inner, box_outer};
    cuuint32_t es[2] = {1, 1};
    fn(m, CU_TENSOR_MAP_DATA_TYPE_BFLOAT16, 2, (void*)ptr, dims, strides, box, es, CU_TENSOR_MAP_INTERLEAVE_NONE, swz,
       CU_TENSOR_MAP_L2_PROMOTION_L2_256B, CU_TENSOR_MAP_FLOAT_OOB_FILL_NONE);
}

extern "C" void kernel_launch(void* const* d_in, const int* in_sizes, int n_in, void* d_out, int out_size) {
    (void)in_sizes; (void)n_in; (void)out_size;
    static Maps m;
    static const void* cached[11] = {0};
    static bool attr_done = false;
    static int grid = 128;
    bool same = true;
    for (int i = 0; i < 11; i++) same = same && (cached[i] == d_in[i]);
    if (!same || !attr_done) {
        void* fnp = nullptr;
        cudaDriverEntryPointQueryResult qr;
        cudaGetDriverEntryPoint("cuTensorMapEncodeTiled", &fnp, cudaEnableDefault, &qr);
        EncodeFn fn = (EncodeFn)fnp;
        void* po = nullptr;
        cudaGetSymbolAddress(&po, g_O);
        encode_2d(fn, &m.x, d_in[0], DM, SEQ, 64, 128);
        encode_2d(fn, &m.wq[0], d_in[1], DM, DM, 64, 64);
        encode_2d(fn, &m.wq[1], d_in[6], DM, DM, 64, 64);
        encode_2d(fn, &m.wkv[0], d_in[2], 16, DM, 8, 256, CU_TENSOR_MAP_SWIZZLE_NONE);
        encode_2d(fn, &m.wkv[1], d_in[3], 16, DM, 8, 256, CU_TENSOR_MAP_SWIZZLE_NONE);
        encode_2d(fn, &m.wkv[2], d_in[7], 16, DM, 8, 256, CU_TENSOR_MAP_SWIZZLE_NONE);
        encode_2d(fn, &m.wkv[3], d_in[8], 16, DM, 8, 256, CU_TENSOR_MAP_SWIZZLE_NONE);
        encode_2d(fn, &m.o, po, DM, 2 * SEQ, 64, 64);
        encode_2d(fn, &m.wo[0], d_in[4], DM, DM, 64, 64);
        encode_2d(fn, &m.wo[1], d_in[9], DM, DM, 64, 64);
        cudaFuncSetAttribute(fused_kernel, cudaFuncAttributeMaxDynamicSharedMemorySize, SMEM_TOTAL);
        int dev = 0, sms = 0;
        cudaGetDevice(&dev);
        cudaDeviceGetAttribute(&sms, cudaDevAttrMultiProcessorCount, dev);
        grid = sms >= 132 ? 132 : 128;
        for (int i = 0; i < 11; i++) cached[i] = d_in[i];
        attr_done = true;
    }
    cudaLaunchAttribute at[1];
    at[0].id = cudaLaunchAttributeCooperative;
    at[0].val.cooperative = 1;
    cudaLaunchConfig_t cfg = {};
    cfg.stream = cudaStreamPerThread;
    cfg.attrs = at;
    cfg.numAttrs = 1;
    cfg.gridDim = dim3(grid);
    cfg.blockDim = dim3(512);
    cfg.dynamicSmemBytes = SMEM_TOTAL;
    cudaLaunchKernelEx(&cfg, fused_kernel, m, (const bf16*)d_in[0], (const bf16*)d_in[10], (const bf16*)d_in[1], (const bf16*)d_in[6],
                       (const bf16*)d_in[4], (const bf16*)d_in[9], (bf16*)d_out);
}
```

```cpp
#include <cuda_runtime.h>
#include <cuda_bf16.h>
#include <cuda.h>
#include <stdint.h>

typedef __nv_bfloat16 bf16;

#define CTR_PAD 32
#define SEQ 2048
#define DM 512
#define ROWS 65536

__device__ __align__(1024) bf16 g_KV[2 * 4 * SEQ * 8];
__device__ __align__(1024) bf16 g_O[2 * ROWS * 16];
__device__ float g_gate[SEQ];
__device__ __align__(128) unsigned char g_qx[128 * 2048];
__device__ __align__(128) float4 g_px[128 * 3 * 128];
__device__ __align__(16) unsigned int g_flag[256];
#define SPLIT_TILE 15
#define NSPLIT 5
__device__ __align__(16) float g_nrm[512];
__device__ __align__(128) unsigned int g_ctr[19 * CTR_PAD];
#define CTR(i) (g_ctr + (i) * CTR_PAD)

__device__ __forceinline__ uint32_t smem_u32(const void* p) { return (uint32_t)__cvta_generic_to_shared(p); }
__device__ __forceinline__ uint64_t make_desc(uint32_t saddr, uint32_t lbo, uint32_t sbo, uint32_t swz) {
    uint64_t d = 0;
    d |= (uint64_t)((saddr & 0x3FFFF) >> 4);
    d |= (uint64_t)((lbo & 0x3FFFF) >> 4) << 16;
    d |= (uint64_t)((sbo & 0x3FFFF) >> 4) << 32;
    d |= (uint64_t)swz << 62;
    return d;
}
__device__ __forceinline__ void wg_fence() { asm volatile("wgmma.fence.sync.aligned;" ::: "memory"); }
__device__ __forceinline__ void wg_commit() { asm volatile("wgmma.commit_group.sync.aligned;" ::: "memory"); }
template <int N> __device__ __forceinline__ void wg_wait() { asm volatile("wgmma.wait_group.sync.aligned %0;" ::"n"(N) : "memory"); }
template <int N> __device__ __forceinline__ void fence_regs(float* d) {
#pragma unroll
    for (int i = 0; i < N; i++) asm volatile("" : "+f"(d[i])::"memory");
}
__device__ __forceinline__ void mbar_init(uint32_t bar, uint32_t cnt) { asm volatile("mbarrier.init.shared::cta.b64 [%0], %1;" ::"r"(bar), "r"(cnt)); }
__device__ __forceinline__ void mbar_expect_tx(uint32_t bar, uint32_t bytes) {
    asm volatile("mbarrier.arrive.expect_tx.shared::cta.b64 _, [%0], %1;" ::"r"(bar), "r"(bytes) : "memory");
}
__device__ __forceinline__ void mbar_arrive(uint32_t bar) { asm volatile("mbarrier.arrive.shared::cta.b64 _, [%0];" ::"r"(bar) : "memory"); }
__device__ __forceinline__ void mbar_wait(uint32_t bar, uint32_t parity) {
    asm volatile(
        "{\n.reg .pred p;\n"
        "WAIT_LOOP:\n"
        "mbarrier.try_wait.parity.shared::cta.b64 p, [%0], %1;\n"
        "@p bra DONE;\n"
        "bra WAIT_LOOP;\n"
        "DONE:\n}" ::"r"(bar), "r"(parity) : "memory");
}
__device__ __forceinline__ void mbar_wait_u(uint32_t bar, uint32_t parity) {
    uint32_t ok;
    do {
        asm volatile(
            "{\n.reg .pred p;\nmbarrier.try_wait.parity.shared::cta.b64 p, [%1], %2;\nselp.u32 %0, 1, 0, p;\n}"
            : "=r"(ok) : "r"(bar), "r"(parity) : "memory");
    } while (!__all_sync(0xffffffffu, ok));
}
__device__ __forceinline__ void bulk_g2s(uint32_t dst, const void* src, uint32_t bytes, uint32_t bar) {
    asm volatile("cp.async.bulk.shared::cluster.global.mbarrier::complete_tx::bytes [%0], [%1], %2, [%3];" ::"r"(dst), "l"(src), "r"(bytes), "r"(bar) : "memory");
}
__device__ __forceinline__ void tma_2d(uint32_t dst, const CUtensorMap* map, int c0, int c1, uint32_t bar) {
    asm volatile("cp.async.bulk.tensor.2d.shared::cluster.global.mbarrier::complete_tx::bytes [%0], [%1, {%3, %4}], [%2];" ::"r"(dst), "l"(map), "r"(bar), "r"(c0), "r"(c1) : "memory");
}
__device__ __forceinline__ void l2_prefetch(const void* p, uint32_t bytes) {
    asm volatile("cp.async.bulk.prefetch.L2.global [%0], %1;" ::"l"(p), "r"(bytes) : "memory");
}
__device__ __forceinline__ void fence_async() { asm volatile("fence.proxy.async;" ::: "memory"); }
__device__ __forceinline__ uint32_t pack_bf16(float lo, float hi) {
    uint32_t r;
    asm("cvt.rn.bf16x2.f32 %0, %1, %2;" : "=r"(r) : "f"(hi), "f"(lo));
    return r;
}
__device__ __forceinline__ float bf_lo(uint32_t u) { return __uint_as_float(u << 16); }
__device__ __forceinline__ float bf_hi(uint32_t u) { return __uint_as_float(u & 0xFFFF0000u); }
__device__ __forceinline__ float bf_round(float x) { return __bfloat162float(__float2bfloat16_rn(x)); }

#define A8(b) "+f"(d[b + 0]), "+f"(d[b + 1]), "+f"(d[b + 2]), "+f"(d[b + 3]), "+f"(d[b + 4]), "+f"(d[b + 5]), "+f"(d[b + 6]), "+f"(d[b + 7])
#define W8(b) "=f"(d[b + 0]), "=f"(d[b + 1]), "=f"(d[b + 2]), "=f"(d[b + 3]), "=f"(d[b + 4]), "=f"(d[b + 5]), "=f"(d[b + 6]), "=f"(d[b + 7])

__device__ __forceinline__ void mma_n8_ss(float* d, uint64_t ad, uint64_t bd) {
    asm volatile("wgmma.mma_async.sync.aligned.m64n8k16.f32.bf16.bf16 {%0,%1,%2,%3}, %4, %5, 1, 1, 1, 0, 1;"
                 : "+f"(d[0]), "+f"(d[1]), "+f"(d[2]), "+f"(d[3])
                 : "l"(ad), "l"(bd));
}
__device__ __forceinline__ void mma_n128_ss(float* d, uint64_t ad, uint64_t bd) {
    asm volatile(
        "wgmma.mma_async.sync.aligned.m64n128k16.f32.bf16.bf16 "
        "{%0,%1,%2,%3,%4,%5,%6,%7,%8,%9,%10,%11,%12,%13,%14,%15,%16,%17,%18,%19,%20,%21,%22,%23,%24,%25,%26,%27,%28,%29,%30,%31,"
        "%32,%33,%34,%35,%36,%37,%38,%39,%40,%41,%42,%43,%44,%45,%46,%47,%48,%49,%50,%51,%52,%53,%54,%55,%56,%57,%58,%59,%60,%61,%62,%63}, "
        "%64, %65, 1, 1, 1, 0, 1;"
        : A8(0), A8(8), A8(16), A8(24), A8(32), A8(40), A8(48), A8(56)
        : "l"(ad), "l"(bd));
}
__device__ __forceinline__ void qk_n64(float* d, const uint32_t* a, uint64_t bd) {
    asm volatile(
        "wgmma.mma_async.sync.aligned.m64n64k16.f32.bf16.bf16 "
        "{%0,%1,%2,%3,%4,%5,%6,%7,%8,%9,%10,%11,%12,%13,%14,%15,%16,%17,%18,%19,%20,%21,%22,%23,%24,%25,%26,%27,%28,%29,%30,%31}, "
        "{%32,%33,%34,%35}, %36, 0, 1, 1, 0;"
        : W8(0), W8(8), W8(16), W8(24)
        : "r"(a[0]), "r"(a[1]), "r"(a[2]), "r"(a[3]), "l"(bd));
}
__device__ __forceinline__ void pv_n24(float* d, const uint32_t* a, uint64_t bd) {
    asm volatile(
        "wgmma.mma_async.sync.aligned.m64n24k16.f32.bf16.bf16 {%0,%1,%2,%3,%4,%5,%6,%7,%8,%9,%10,%11}, {%12,%13,%14,%15}, %16, 1, 1, 1, 1;"
        : A8(0), "+f"(d[8]), "+f"(d[9]), "+f"(d[10]), "+f"(d[11])
        : "r"(a[0]), "r"(a[1]), "r"(a[2]), "r"(a[3]), "l"(bd));
}

__device__ __forceinline__ float ex2(float x) {
    float e;
    asm("ex2.approx.ftz.f32 %0, %1;" : "=f"(e) : "f"(x));
    return e;
}
__device__ __forceinline__ uint32_t exp_pair_mufu(float x0, float x1) { return pack_bf16(ex2(x0), ex2(x1)); }

#define MAGIC0 (98304.0f + 127.0f - 75.0f / 128.0f)
#define MAGIC1 (MAGIC0 - 143.5f)
__device__ __forceinline__ uint32_t exp_pair_poly(float x0, float x1, uint32_t c3f) {
    const float t0 = x0 + MAGIC0;
    const float t1 = x1 + MAGIC1;
    const uint32_t L = __float_as_uint(t1) * 65536u + __float_as_uint(t0);
    uint32_t y2, r;
    asm("lop3.b32 %0, %1, 0x007F007F, %2, 0xEA;" : "=r"(y2) : "r"(L), "r"(c3f));
    const uint32_t E = L & 0x7F807F80u;
    asm("fma.rn.bf16x2 %0, %1, %2, %3;" : "=r"(r) : "r"(L), "r"(y2), "r"(E));
    return r;
}
#define EXP_MASK 0x2525u
template <int BASE>
__device__ __forceinline__ void exp_half(const float* s, uint32_t* p, uint32_t c3f) {
#pragma unroll
    for (int i = 0; i < 8; i++) {
        if ((EXP_MASK >> (BASE + i)) & 1) p[i] = exp_pair_mufu(s[2 * i], s[2 * i + 1]);
        else p[i] = exp_pair_poly(s[2 * i], s[2 * i + 1], c3f);
    }
}

struct Maps {
    CUtensorMap x;
    CUtensorMap wq[2];
    CUtensorMap wkv[4];
    CUtensorMap o;
    CUtensorMap wo[2];
};
#define SM_X 20480
#define SM_WKV 151552
#define SM_WQ 159744
#define CHUNK_BYTES 20480
#define SM_Q 163840
#define C_STAGES 4
#define C_STAGE_BYTES 49152
#define SM_XCH 196608
#define SM_BAR 225280
#define BAR_X (SM_BAR)
#define BAR_KV (SM_BAR + 64)
#define BAR_CF (SM_BAR + 128)
#define BAR_CE (SM_BAR + 192)
#define BAR_WF (SM_BAR + 256)
#define BAR_WE (SM_BAR + 288)
#define BAR_WKV (SM_BAR + 320)
#define SM_MISC (SM_BAR + 384)
#define SMEM_TOTAL (SM_BAR + 1024 + 1024)

__device__ __forceinline__ void spin_until(const unsigned int* ctr, unsigned int target) {
    unsigned int v;
    for (unsigned int it = 0; it < (1u << 23); it++) {
        asm volatile("ld.acquire.gpu.global.u32 %0, [%1];" : "=r"(v) : "l"(ctr) : "memory");
        if (v >= target) return;
    }
    __trap();
}
__device__ __forceinline__ void signal(unsigned int* ctr) {
    asm volatile("red.release.gpu.global.add.u32 [%0], 1;" ::"l"(ctr) : "memory");
}

__device__ __forceinline__ void attn_tile_slow(const uint32_t* qq, uint64_t kd0, uint64_t vd0, float* o, float* s, uint32_t* p) {
    float m0 = -INFINITY, m1 = -INFINITY;
#pragma unroll 1
    for (int ch = 0; ch < 32; ch++) {
        wg_fence();
        qk_n64(s, qq, kd0 + (uint64_t)((ch >> 2) * 1280 + (ch & 3) * 64));
        wg_commit();
        wg_wait<0>();
        fence_regs<32>(s);
#pragma unroll
        for (int j = 0; j < 8; j++) {
            m0 = fmaxf(m0, fmaxf(s[4 * j], s[4 * j + 1]));
            m1 = fmaxf(m1, fmaxf(s[4 * j + 2], s[4 * j + 3]));
        }
    }
    m0 = fmaxf(m0, __shfl_xor_sync(0xffffffffu, m0, 1));
    m1 = fmaxf(m1, __shfl_xor_sync(0xffffffffu, m1, 1));
    m0 = fmaxf(m0, __shfl_xor_sync(0xffffffffu, m0, 2));
    m1 = fmaxf(m1, __shfl_xor_sync(0xffffffffu, m1, 2));
#pragma unroll 1
    for (int ch = 0; ch < 32; ch++) {
        wg_fence();
        qk_n64(s, qq, kd0 + (uint64_t)((ch >> 2) * 1280 + (ch & 3) * 64));
        wg_commit();
        wg_wait<0>();
        fence_regs<32>(s);
#pragma unroll
        for (int j = 0; j < 8; j++) {
            p[2 * j] = exp_pair_mufu(s[4 * j] - m0, s[4 * j + 1] - m0);
            p[2 * j + 1] = exp_pair_mufu(s[4 * j + 2] - m1, s[4 * j + 3] - m1);
        }
        wg_fence();
#pragma unroll
        for (int j = 0; j < 4; j++) pv_n24(o, p + 4 * j, vd0 + (uint64_t)((ch >> 2) * 1280 + (ch & 3) * 64 + 16 * j));
        wg_commit();
        wg_wait<0>();
        fence_regs<12>(o);
    }
}

#define TILE_OF(w, t) ((w) * 4 + (t))
#define UNIT_CTA(t) (helper ? (((wg * 8 + (t)) >> 2) * 2 + (int)(blockIdx.x & 1)) * 8 + br * 4 + ((t) & 3) : (int)blockIdx.x)
#define LOAD_Q(t)                                                                                                        \
    {                                                                                                                    \
        const unsigned char* qp = (helper ? g_qx + cta * 2048 : smem + SM_Q + TILE_OF(wg, t) * 2048) + ((tid >> 5) & 3) * 512 + (tid & 31) * 8; \
        asm volatile("ld.volatile.v2.u32 {%0, %1}, [%2];" : "=r"(q[0]), "=r"(q[2]) : "l"(qp) : "memory");                \
        asm volatile("ld.volatile.v2.u32 {%0, %1}, [%2];" : "=r"(q[1]), "=r"(q[3]) : "l"(qp + 256) : "memory");          \
    }
__device__ __forceinline__ void finish() {
    __threadfence();
    if (atomicAdd(CTR(18), 1u) == gridDim.x - 1) {
        for (int i = 0; i < 19; i++) *CTR(i) = 0u;
        for (int i = 0; i < 256; i += 4) *(uint4*)(g_flag + i) = make_uint4(0, 0, 0, 0);
    }
}
__device__ __forceinline__ void store_o(const float* o, int cta, int tile) {
    const int mb = cta >> 3, nb = cta & 7, br = nb >> 2;
    int tid2;
    asm volatile("mov.u32 %0, %%tid.x;" : "=r"(tid2));
    const int lane = tid2 & 31;
    const float l0 = __shfl_sync(0xffffffffu, o[8], lane & ~3);
    const float l1 = __shfl_sync(0xffffffffu, o[10], lane & ~3);
    const float i0 = 1.f / l0, i1 = 1.f / l1;
    const uint32_t row = (uint32_t)(br * SEQ + mb * 128 + (tile & 1) * 64 + ((tid2 >> 5) & 3) * 16 + (lane >> 2));
    bf16* op = g_O + row * DM + ((nb & 3) * 8 + (tile >> 1)) * 16 + (lane & 3) * 2;
    *(uint32_t*)(op) = pack_bf16(o[0] * i0, o[1] * i0);
    *(uint32_t*)(op + 8 * DM) = pack_bf16(o[2] * i1, o[3] * i1);
    *(uint32_t*)(op + 8) = pack_bf16(o[4] * i0, o[5] * i0);
    *(uint32_t*)(op + 8 * DM + 8) = pack_bf16(o[6] * i1, o[7] * i1);
}

__global__ void __launch_bounds__(512, 1) fused_kernel(const __grid_constant__ Maps maps, const bf16* __restrict__ x, const bf16* __restrict__ gate_w,
                                                        const bf16* __restrict__ wqa, const bf16* __restrict__ wqb, const bf16* __restrict__ woa,
                                                        const bf16* __restrict__ wob, bf16* __restrict__ out) {
    const bool split = gridDim.x > 128;
    const bool helper = blockIdx.x >= 128;
    extern __shared__ unsigned char smem_raw[];
    const uint32_t sb = (smem_u32(smem_raw) + 1023) & ~1023u;
    unsigned char* smem = smem_raw + (sb - smem_u32(smem_raw));
    const int tid = threadIdx.x;
    const int wg = __shfl_sync(0xffffffffu, tid >> 7, 0);
    const int mb = blockIdx.x >> 3, nb = blockIdx.x & 7;
    const int br = helper ? (int)((blockIdx.x >> 1) & 1) : nb >> 2;
    if (tid == 384 && !helper) {
        for (int i = 0; i < 8; i++) mbar_init(sb + BAR_X + i * 8, 1);
        mbar_init(sb + BAR_WKV, 1);
        asm volatile("fence.mbarrier_init.release.cluster;" ::: "memory");
        mbar_expect_tx(sb + BAR_WKV, 8192);
        tma_2d(sb + SM_WKV, &maps.wkv[nb >> 1], (nb & 1) * 8, 0, sb + BAR_WKV);
        tma_2d(sb + SM_WKV + 4096, &maps.wkv[nb >> 1], (nb & 1) * 8, 256, sb + BAR_WKV);
        for (int kb = 0; kb < 8; kb++) {
            mbar_expect_tx(sb + BAR_X + kb * 8, 16384);
            tma_2d(sb + SM_X + kb * 16384, &maps.x, kb * 64, mb * 128, sb + BAR_X + kb * 8);
        }
    }
    if (tid == 352) asm volatile("prefetch.tensormap [%0];" ::"l"(&maps.x) : "memory");
    if (tid == 0) {
        for (int i = 0; i < 8; i++) {
            mbar_init(sb + BAR_KV + i * 8, 1);
            mbar_init(sb + BAR_CF + i * 8, 1);
            mbar_init(sb + BAR_CE + i * 8, 4);
        }
        for (int i = 0; i < 4; i++) {
            mbar_init(sb + BAR_WF + i * 8, 1);
            mbar_init(sb + BAR_WE + i * 8, 8);
        }
        asm volatile("fence.mbarrier_init.release.cluster;" ::: "memory");
    }
    if (tid == 416 && !helper) {
        l2_prefetch(wqa + (size_t)blockIdx.x * 2048, 4096);
        l2_prefetch(wqb + (size_t)blockIdx.x * 2048, 4096);
        asm volatile("prefetch.tensormap [%0];" ::"l"(&maps.wq[br]) : "memory");
        asm volatile("prefetch.tensormap [%0];" ::"l"(&maps.o) : "memory");
        asm volatile("prefetch.tensormap [%0];" ::"l"(&maps.wo[0]) : "memory");
        asm volatile("prefetch.tensormap [%0];" ::"l"(&maps.wo[1]) : "memory");
    }
    __syncthreads();

    const unsigned char* kv_src = (const unsigned char*)g_KV + (size_t)br * 131072;
    if (helper) {
#pragma unroll
        for (int i = 0; i < 4; i++) *(uint4*)(smem + (2 * i + (tid >> 8)) * CHUNK_BYTES + 16384 + (tid & 255) * 16) = make_uint4(0x00003F80u, 0, 0, 0);
        asm volatile("fence.proxy.async.shared::cta;" ::: "memory");
    }
    if (helper && wg < 3) {
    } else if (wg < 2) {
        const int warp = tid >> 5, lane = tid & 31;
        float acc[64];
#pragma unroll
        for (int i = 0; i < 64; i++) acc[i] = 0.f;
        fence_regs<64>(acc);
        asm volatile("bar.sync 3, 384;" ::: "memory");
#pragma unroll
        for (int kb = 0; kb < 8; kb++) {
            const int st = kb & 3;
            mbar_wait_u(sb + BAR_WF + st * 8, kb >> 2);
            const uint64_t ad = make_desc(sb + SM_X + kb * 16384 + wg * 8192, 16, 1024, 1);
            const uint64_t bd = make_desc(sb + SM_WQ + st * 16384, 8192, 1024, 1);
            wg_fence();
#pragma unroll
            for (int kk = 0; kk < 4; kk++) mma_n128_ss(acc, ad + kk * 2, bd + kk * 128);
            wg_commit();
            if (kb >= 1 && kb <= 4) {
                wg_wait<1>();
                if (lane == 0) mbar_arrive(sb + BAR_WE + (kb - 1) * 8);
            }
        }
        wg_wait<0>();
        fence_regs<64>(acc);
        asm volatile("bar.sync 1, 384;" ::: "memory");
        const int r = lane >> 2, c = lane & 3;
        const float qs = 0.25f * 1.4426950408889634f;
        unsigned char* qp = smem + SM_Q + wg * 2048 + ((warp & 3) * 16 + r) * 32 + c * 8;
#pragma unroll
        for (int h = 0; h < 8; h++) {
            const float* a = acc + h * 8;
            *(uint2*)(qp + h * 4096) = make_uint2(pack_bf16(a[0] * qs, a[1] * qs), pack_bf16(a[4] * qs, a[5] * qs));
            *(uint2*)(qp + h * 4096 + 256) = make_uint2(pack_bf16(a[2] * qs, a[3] * qs), pack_bf16(a[6] * qs, a[7] * qs));
        }
    } else if (wg == 2) {
        const int warp = (tid >> 5) & 3, lane = tid & 31;
        float a0[4] = {0.f, 0.f, 0.f, 0.f}, a1[4] = {0.f, 0.f, 0.f, 0.f};
        fence_regs<4>(a0);
        fence_regs<4>(a1);
        *(uint4*)(smem + 16384 + (tid & 127) * 16) = make_uint4(0x00003F80u, 0, 0, 0);
        *(uint4*)(smem + 18432 + (tid & 127) * 16) = make_uint4(0x00003F80u, 0, 0, 0);
        mbar_wait_u(sb + BAR_WKV, 0);
#pragma unroll
        for (int kb = 0; kb < 8; kb++) {
            mbar_wait_u(sb + BAR_X + kb * 8, 0);
            const uint64_t ad = make_desc(sb + SM_X + kb * 16384, 16, 1024, 1);
            const uint64_t bd = make_desc(sb + SM_WKV + kb * 1024, 128, 128, 0);
            wg_fence();
#pragma unroll
            for (int kk = 0; kk < 4; kk++) {
                mma_n8_ss(a0, ad + kk * 2, bd + kk * 16);
                mma_n8_ss(a1, ad + 512 + kk * 2, bd + kk * 16);
            }
            wg_commit();
        }
        wg_wait<0>();
        fence_regs<4>(a0);
        fence_regs<4>(a1);
        asm volatile("bar.arrive 3, 384;" ::: "memory");
        const int r = lane >> 2, c = lane & 3;
        const int row = mb * 128 + warp * 16 + r;
        const uint32_t k0 = pack_bf16(a0[0], a0[1]), k1 = pack_bf16(a0[2], a0[3]);
        const uint32_t k2 = pack_bf16(a1[0], a1[1]), k3 = pack_bf16(a1[2], a1[3]);
        bf16* kvp = g_KV + (size_t)br * 65536 + (row >> 8) * 8192 + (nb & 3) * 2048 + (row & 255) * 8 + 2 * c;
        *(uint32_t*)kvp = k0;
        *(uint32_t*)(kvp + 64) = k1;
        *(uint32_t*)(kvp + 512) = k2;
        *(uint32_t*)(kvp + 576) = k3;
        unsigned int mu;
        if (((nb >> 1) & 1) == 0) {
            float n0 = bf_lo(k0) * bf_lo(k0) + bf_hi(k0) * bf_hi(k0);
            float n1 = bf_lo(k1) * bf_lo(k1) + bf_hi(k1) * bf_hi(k1);
            float n2 = bf_lo(k2) * bf_lo(k2) + bf_hi(k2) * bf_hi(k2);
            float n3 = bf_lo(k3) * bf_lo(k3) + bf_hi(k3) * bf_hi(k3);
#pragma unroll
            for (int sft = 1; sft <= 2; sft <<= 1) {
                n0 += __shfl_xor_sync(0xffffffffu, n0, sft);
                n1 += __shfl_xor_sync(0xffffffffu, n1, sft);
                n2 += __shfl_xor_sync(0xffffffffu, n2, sft);
                n3 += __shfl_xor_sync(0xffffffffu, n3, sft);
            }
            mu = max(max(__float_as_uint(n0), __float_as_uint(n1)), max(__float_as_uint(n2), __float_as_uint(n3)));
        } else {
            mu = max(max(max((k0 << 16) & 0x7FFFFFFFu, k0 & 0x7FFF0000u), max((k1 << 16) & 0x7FFFFFFFu, k1 & 0x7FFF0000u)),
                     max(max((k2 << 16) & 0x7FFFFFFFu, k2 & 0x7FFF0000u), max((k3 << 16) & 0x7FFFFFFFu, k3 & 0x7FFF0000u)));
        }
        mu = __reduce_max_sync(0xffffffffu, mu);
        __syncwarp();
        if (lane == 0) {
            g_nrm[(nb * 16 + mb) * 4 + warp] = __uint_as_float(mu);
            signal(CTR(br));
        }
        asm volatile("bar.sync 1, 384;" ::: "memory");
#pragma unroll
        for (int i = 1; i < 8; i++) {
            *(uint4*)(smem + i * CHUNK_BYTES + 16384 + (tid & 127) * 16) = make_uint4(0x00003F80u, 0, 0, 0);
            *(uint4*)(smem + i * CHUNK_BYTES + 18432 + (tid & 127) * 16) = make_uint4(0x00003F80u, 0, 0, 0);
        }
        asm volatile("fence.proxy.async.shared::cta;" ::: "memory");
    } else {
        const int lane = tid & 31, w = (tid >> 5) & 3;
        if (w == 0) {
            if (lane == 0) {
                if (!helper) {
                    mbar_wait(sb + BAR_X + 56, 0);
                    for (int st = 0; st < 4; st++) {
                        mbar_expect_tx(sb + BAR_WF + st * 8, 16384);
                        tma_2d(sb + SM_WQ + st * 16384, &maps.wq[br], (nb & 3) * 128, st * 64, sb + BAR_WF + st * 8);
                        tma_2d(sb + SM_WQ + st * 16384 + 8192, &maps.wq[br], (nb & 3) * 128 + 64, st * 64, sb + BAR_WF + st * 8);
                    }
                    for (int st = 0; st < 4; st++) {
                        mbar_wait(sb + BAR_WE + st * 8, 0);
                        mbar_expect_tx(sb + BAR_WF + st * 8, 16384);
                        tma_2d(sb + SM_WQ + st * 16384, &maps.wq[br], (nb & 3) * 128, (st + 4) * 64, sb + BAR_WF + st * 8);
                        tma_2d(sb + SM_WQ + st * 16384 + 8192, &maps.wq[br], (nb & 3) * 128 + 64, (st + 4) * 64, sb + BAR_WF + st * 8);
                    }
                    l2_prefetch(woa + (size_t)blockIdx.x * 2048, 4096);
                    l2_prefetch(wob + (size_t)blockIdx.x * 2048, 4096);
                }
                spin_until(CTR(br), 256);
                fence_async();
                if (!helper) {
                    mbar_expect_tx(sb + BAR_KV, 16384);
                    bulk_g2s(sb, kv_src, 16384, sb + BAR_KV);
                }
            }
            __syncwarp();
            const uint4 hk = __ldcg((const uint4*)g_nrm + br * 64 + lane);
            const uint4 hv = __ldcg((const uint4*)g_nrm + br * 64 + 32 + lane);
            unsigned int h = max(max(hk.x, hk.y), max(hk.z, hk.w));
            const unsigned int nv = max(max(hv.x, hv.y), max(hv.z, hv.w));
#pragma unroll
            for (int sft = 8; sft > 0; sft >>= 1) h = max(h, __shfl_xor_sync(0xffffffffu, h, sft));
            float kmax2 = __uint_as_float(h) + __uint_as_float(__shfl_xor_sync(0xffffffffu, h, 16));
            const float vmax = __uint_as_float(__reduce_max_sync(0xffffffffu, nv));
            if (!(vmax <= 1.0e15f)) kmax2 = __uint_as_float(0x7FC00000u);
            if (lane == 0) *(volatile float*)(smem + SM_MISC + 4) = kmax2;
        } else if (!helper) {
            const uint4* gw = (const uint4*)(gate_w + lane * 16);
            const uint4 w0 = __ldg(gw), w1 = __ldg(gw + 1);
            const uint32_t wv[8] = {w0.x, w0.y, w0.z, w0.w, w1.x, w1.y, w1.z, w1.w};
            uint4 xa[6][2];
#pragma unroll
            for (int rr = 0; rr < 6; rr++) {
                const int lr = min(w - 1 + rr * 3, 15);
                const uint4* xp = (const uint4*)(x + (size_t)(blockIdx.x * 16 + lr) * DM + lane * 16);
                xa[rr][0] = __ldg(xp);
                xa[rr][1] = __ldg(xp + 1);
            }
#pragma unroll
            for (int rr = 0; rr < 6; rr++) {
                const uint32_t xv[8] = {xa[rr][0].x, xa[rr][0].y, xa[rr][0].z, xa[rr][0].w, xa[rr][1].x, xa[rr][1].y, xa[rr][1].z, xa[rr][1].w};
                float sum = 0.f;
#pragma unroll
                for (int i = 0; i < 8; i++) {
                    sum += bf_round(bf_lo(xv[i]) * bf_lo(wv[i]));
                    sum += bf_round(bf_hi(xv[i]) * bf_hi(wv[i]));
                }
#pragma unroll
                for (int o = 16; o > 0; o >>= 1) sum += __shfl_xor_sync(0xffffffffu, sum, o);
                if (lane == 0) {
                    sum = bf_round(sum);
                    g_gate[blockIdx.x * 16 + min(w - 1 + rr * 3, 15)] = bf_round(1.f / (1.f + __expf(-sum)));
                }
            }
        }
    }
    __syncthreads();
    if (tid == 384) {
        for (int g = helper ? NSPLIT : 1; g < 8; g++) {
            mbar_expect_tx(sb + BAR_KV + g * 8, 16384);
            bulk_g2s(sb + g * CHUNK_BYTES, kv_src + g * 16384, 16384, sb + BAR_KV + g * 8);
        }
    }
    __syncwarp();

    {
        uint32_t c3f = 0x3F003F00u;
        asm volatile("" : "+r"(c3f));
        const uint64_t kd0 = make_desc(sb, 4096, 128, 0);
        const uint64_t vd0 = make_desc(sb + 8192, 128, 4096, 0);
        if (split && !helper && wg == 3) {
            *(uint4*)(g_qx + blockIdx.x * 2048 + (tid & 127) * 16) = *(const uint4*)(smem + SM_Q + SPLIT_TILE * 2048 + (tid & 127) * 16);
            asm volatile("bar.sync 4, 128;" ::: "memory");
            if (tid == 480) signal(&g_flag[blockIdx.x]);
            __syncwarp();
        }
        const int nunits = helper ? 8 : 4;
#pragma unroll 1
        for (int t = 0; t < nunits; t++) {
            const int cta = UNIT_CTA(t);
            const bool merge = split && !helper && wg == 3 && t == 3;
            const uint32_t g0 = helper ? NSPLIT : 0, g1 = merge ? NSPLIT : 8;
            uint32_t q[4];
            if (helper) {
                if ((tid & 127) == 0) spin_until(&g_flag[cta], 1);
                asm volatile("bar.sync %0, 128;" ::"r"(wg + 1) : "memory");
            }
            LOAD_Q(t)
            float o[12];
            float s0[32], s1[32];
            uint32_t p[16];
#pragma unroll
            for (int i = 0; i < 12; i++) o[i] = 0.f;
            fence_regs<12>(o);
            {
                uint32_t kvbar = sb + BAR_KV + g0 * 8;
                uint64_t kd = kd0 + g0 * 1280, vd = vd0 + g0 * 1280;
                mbar_wait_u(kvbar, 0);
                kvbar += 8;
                wg_fence();
                qk_n64(s0, q, kd);
                wg_commit();
                wg_wait<0>();
                fence_regs<32>(s0);
#define HALF_STEP(SC, SN, P, KOFF, VOFF)              \
    exp_half<0>(SC, P, c3f);                         \
    wg_wait<0>();                                    \
    wg_fence();                                      \
    qk_n64(SN, q, kd + (KOFF));                      \
    wg_commit();                                     \
    pv_n24(o, P, vd + (VOFF));                       \
    pv_n24(o, P + 4, vd + (VOFF) + 16);              \
    wg_commit();                                     \
    exp_half<8>(SC + 16, P + 8, c3f);                \
    wg_fence();                                      \
    pv_n24(o, P + 8, vd + (VOFF) + 32);              \
    pv_n24(o, P + 12, vd + (VOFF) + 48);             \
    wg_commit();                                     \
    wg_wait<2>();                                    \
    fence_regs<32>(SN);
                uint32_t p2[16];
#pragma unroll 1
                for (uint32_t g = g0; g < g1; g++) {
                    if (t == 0 && g < 7) mbar_wait_u(kvbar, 0);
                    kvbar += 8;
                    HALF_STEP(s0, s1, p, 64, 0)
                    HALF_STEP(s1, s0, p2, 128, 64)
                    HALF_STEP(s0, s1, p, 192, 128)
                    HALF_STEP(s1, s0, p2, 1280, 192)
                    kd += 1280;
                    vd += 1280;
                }
                wg_wait<0>();
                fence_regs<12>(o);
            }
            int tid2;
            asm volatile("mov.u32 %0, %%tid.x;" : "=r"(tid2));
            volatile uint32_t* redo = (volatile uint32_t*)(smem + SM_MISC + 16) + (tid2 >> 5) * 8;
            if (helper) {
                if (t > 0 && (tid2 & 127) == 96) signal(&g_flag[128 + UNIT_CTA(t - 1)]);
                __syncwarp();
                float4* pp = g_px + cta * 384 + (tid2 & 127);
                pp[0] = make_float4(o[0], o[1], o[2], o[3]);
                pp[128] = make_float4(o[4], o[5], o[6], o[7]);
                pp[256] = make_float4(o[8], o[9], o[10], o[11]);
                continue;
            }
            if (merge) {
                if ((tid2 & 127) == 0) spin_until(&g_flag[128 + cta], 1);
                asm volatile("bar.sync 4, 128;" ::: "memory");
                const float4* pp = g_px + cta * 384 + (tid2 & 127);
                const float4 a = __ldcg(pp), b = __ldcg(pp + 128), c = __ldcg(pp + 256);
                o[0] += a.x; o[1] += a.y; o[2] += a.z; o[3] += a.w;
                o[4] += b.x; o[5] += b.y; o[6] += b.z; o[7] += b.w;
                o[8] += c.x; o[10] += c.z;
            }
            uint32_t any_unsafe;
            {
                float n0 = bf_lo(q[0]) * bf_lo(q[0]) + bf_hi(q[0]) * bf_hi(q[0]) + bf_lo(q[2]) * bf_lo(q[2]) + bf_hi(q[2]) * bf_hi(q[2]);
                float n1 = bf_lo(q[1]) * bf_lo(q[1]) + bf_hi(q[1]) * bf_hi(q[1]) + bf_lo(q[3]) * bf_lo(q[3]) + bf_hi(q[3]) * bf_hi(q[3]);
                n0 += __shfl_xor_sync(0xffffffffu, n0, 1);
                n1 += __shfl_xor_sync(0xffffffffu, n1, 1);
                n0 += __shfl_xor_sync(0xffffffffu, n0, 2);
                n1 += __shfl_xor_sync(0xffffffffu, n1, 2);
                const float kmax2 = *(volatile float*)(smem + SM_MISC + 4);
                const bool unsafe = !(n0 * kmax2 <= 3600.f) || !(n1 * kmax2 <= 3600.f);
                asm volatile(
                    "{\n.reg .pred p, q;\nsetp.ne.u32 q, %1, 0;\nbar.red.or.pred p, %2, 128, q;\nselp.u32 %0, 1, 0, p;\n}"
                    : "=r"(any_unsafe) : "r"((uint32_t)unsafe), "r"(wg + 1) : "memory");
                if ((tid2 & 31) == 0) redo[t] = any_unsafe;
            }
            store_o(o, cta, TILE_OF(wg, t));
        }
        __syncwarp();
        if (helper) {
            asm volatile("bar.sync %0, 128;" ::"r"(wg + 1) : "memory");
            if ((tid & 127) == 96) signal(&g_flag[128 + UNIT_CTA(7)]);
            __syncwarp();
        }
#pragma unroll 1
        for (int t = 0; t < (helper ? 0 : 4); t++) {
            if (!__any_sync(0xffffffffu, ((volatile uint32_t*)(smem + SM_MISC + 16))[(tid >> 5) * 8 + t])) continue;
            const int cta = UNIT_CTA(t);
            uint32_t q[4];
            LOAD_Q(t)
            float o[12], s0[32];
            uint32_t p[16];
#pragma unroll
            for (int i = 0; i < 12; i++) o[i] = 0.f;
            fence_regs<12>(o);
            attn_tile_slow(q, kd0, vd0, o, s0, p);
            store_o(o, cta, TILE_OF(wg, t));
        }
    }
    if (helper) {
        __syncthreads();
        if (tid == 0) finish();
        return;
    }
    asm volatile("fence.proxy.async.shared::cta;" ::: "memory");
    asm volatile("bar.sync %0, 128;" ::"r"(wg + 1) : "memory");
    if (((tid >> 5) & 3) == 3) {
        asm volatile("bar.arrive 0, 512;" ::: "memory");
        if ((tid & 31) == 0) signal(CTR(2 + mb));
        __syncwarp();
    } else {
        asm volatile("bar.sync 0, 512;" ::: "memory");
    }

    const int orow0 = mb * 128 + (nb >> 2) * 64, ocol0 = (nb & 3) * 128;
    if (wg == 2) {
        if (tid == 288) {
            for (int i = 0; i < 2 * C_STAGES; i++) {
                const int st = i >> 1, b = i & 1;
                const uint32_t s0 = sb + st * C_STAGE_BYTES + b * 24576;
                mbar_expect_tx(sb + BAR_CF + i * 8, 24576);
                tma_2d(s0 + 8192, &maps.wo[b], ocol0, st * 128, sb + BAR_CF + i * 8);
                tma_2d(s0 + 16384, &maps.wo[b], ocol0 + 64, st * 128, sb + BAR_CF + i * 8);
            }
        }
        if (tid == 256) {
            spin_until(CTR(2 + mb), 32);
            fence_async();
            for (int i = 0; i < 2 * C_STAGES; i++) {
                const int st = i >> 1, b = i & 1;
                tma_2d(sb + st * C_STAGE_BYTES + b * 24576, &maps.o, st * 128, b * SEQ + orow0, sb + BAR_CF + i * 8);
            }
            for (int i = 0; i < 2 * C_STAGES; i++) {
                const int st = i >> 1, b = i & 1;
                const uint32_t s0 = sb + st * C_STAGE_BYTES + b * 24576;
                mbar_wait(sb + BAR_CE + i * 8, 0);
                mbar_expect_tx(sb + BAR_CF + i * 8, 24576);
                tma_2d(s0 + 8192, &maps.wo[b], ocol0, st * 128 + 64, sb + BAR_CF + i * 8);
                tma_2d(s0 + 16384, &maps.wo[b], ocol0 + 64, st * 128 + 64, sb + BAR_CF + i * 8);
                tma_2d(s0, &maps.o, st * 128 + 64, b * SEQ + orow0, sb + BAR_CF + i * 8);
            }
            finish();
        }
    } else if (wg < 2) {
        const int warp = tid >> 5, lane = tid & 31;
        float acc[64];
#pragma unroll
        for (int i = 0; i < 64; i++) acc[i] = 0.f;
        fence_regs<64>(acc);
        const int r = lane >> 2, c = lane & 3;
        const int lrow = (warp & 3) * 16 + r;
        float g0 = 0.f, g1 = 0.f;
#pragma unroll
        for (int kb = 0; kb < 8; kb++) {
            const int st = kb % C_STAGES;
            const uint32_t s0 = sb + st * C_STAGE_BYTES + wg * 24576;
            mbar_wait_u(sb + BAR_CF + (st * 2 + wg) * 8, kb >= C_STAGES ? 1 : 0);
            if (kb == 0) {
                g0 = __ldcg(g_gate + orow0 + lrow);
                g1 = __ldcg(g_gate + orow0 + lrow + 8);
            }
            const uint64_t ad = make_desc(s0, 16, 1024, 1);
            const uint64_t bd = make_desc(s0 + 8192, 8192, 1024, 1);
            wg_fence();
#pragma unroll
            for (int kk = 0; kk < 4; kk++) mma_n128_ss(acc, ad + kk * 2, bd + kk * 128);
            wg_commit();
            if (kb >= 1 && kb <= C_STAGES) {
                wg_wait<1>();
                if (lane == 0) mbar_arrive(sb + BAR_CE + ((kb - 1) * 2 + wg) * 8);
            }
        }
        wg_wait<0>();
        fence_regs<64>(acc);
        if (wg) { g0 = bf_round(1.f - g0); g1 = bf_round(1.f - g1); }
        uint32_t t[32];
#pragma unroll
        for (int j = 0; j < 16; j++) {
            t[2 * j] = pack_bf16(g0 * bf_round(acc[4 * j]), g0 * bf_round(acc[4 * j + 1]));
            t[2 * j + 1] = pack_bf16(g1 * bf_round(acc[4 * j + 2]), g1 * bf_round(acc[4 * j + 3]));
        }
        uint32_t* xch = (uint32_t*)(smem + SM_XCH);
        const int lt = tid & 127;
#pragma unroll
        for (int j = 0; j < 16; j++) xch[(wg * 16 + j) * 128 + lt] = wg ? t[j] : t[16 + j];
        asm volatile("bar.sync 1, 256;" ::: "memory");
        unsigned char* ot = smem + wg * 16384;
#pragma unroll
        for (int j = 0; j < 16; j++) {
            const uint32_t mine = wg ? t[16 + j] : t[j];
            const uint32_t other = xch[((wg ^ 1) * 16 + j) * 128 + lt];
            const uint32_t v = pack_bf16(bf_lo(mine) + bf_lo(other), bf_hi(mine) + bf_hi(other));
            *(uint32_t*)(ot + (lrow + (j & 1) * 8) * 144 + (j >> 1) * 16 + c * 4) = v;
        }
        asm volatile("bar.sync %0, 128;" ::"r"(wg + 2) : "memory");
#pragma unroll
        for (int i = 0; i < 4; i++) {
            const int idx = i * 128 + lt, row = idx >> 3, ch = idx & 7;
            const uint4 v = *(const uint4*)(ot + row * 144 + ch * 16);
            *(uint4*)(out + (size_t)(orow0 + row) * DM + ocol0 + wg * 64 + ch * 8) = v;
        }
    }
}

typedef CUresult (*EncodeFn)(CUtensorMap*, CUtensorMapDataType, cuuint32_t, void*, const cuuint64_t*, const cuuint64_t*, const cuuint32_t*,
                             const cuuint32_t*, CUtensorMapInterleave, CUtensorMapSwizzle, CUtensorMapL2promotion, CUtensorMapFloatOOBfill);

static void encode_2d(EncodeFn fn, CUtensorMap* m, const void* ptr, uint64_t inner, uint64_t outer, uint32_t box_inner, uint32_t box_outer,
                      CUtensorMapSwizzle swz = CU_TENSOR_MAP_SWIZZLE_128B) {
    cuuint64_t dims[2] = {inner, outer};
    cuuint64_t strides[1] = {inner * 2};
    cuuint32_t box[2] = {box_inner, box_outer};
    cuuint32_t es[2] = {1, 1};
    fn(m, CU_TENSOR_MAP_DATA_TYPE_BFLOAT16, 2, (void*)ptr, dims, strides, box, es, CU_TENSOR_MAP_INTERLEAVE_NONE, swz,
       CU_TENSOR_MAP_L2_PROMOTION_L2_256B, CU_TENSOR_MAP_FLOAT_OOB_FILL_NONE);
}

extern "C" void kernel_launch(void* const* d_in, const int* in_sizes, int n_in, void* d_out, int out_size) {
    (void)in_sizes; (void)n_in; (void)out_size;
    static Maps m;
    static const void* cached[11] = {0};
    static bool attr_done = false;
    static int grid = 128;
    bool same = true;
    for (int i = 0; i < 11; i++) same = same && (cached[i] == d_in[i]);
    if (!same || !attr_done) {
        void* fnp = nullptr;
        cudaDriverEntryPointQueryResult qr;
        cudaGetDriverEntryPoint("cuTensorMapEncodeTiled", &fnp, cudaEnableDefault, &qr);
        EncodeFn fn = (EncodeFn)fnp;
        void* po = nullptr;
        cudaGetSymbolAddress(&po, g_O);
        encode_2d(fn, &m.x, d_in[0], DM, SEQ, 64, 128);
        encode_2d(fn, &m.wq[0], d_in[1], DM, DM, 64, 64);
        encode_2d(fn, &m.wq[1], d_in[6], DM, DM, 64, 64);
        encode_2d(fn, &m.wkv[0], d_in[2], 16, DM, 8, 256, CU_TENSOR_MAP_SWIZZLE_NONE);
        encode_2d(fn, &m.wkv[1], d_in[3], 16, DM, 8, 256, CU_TENSOR_MAP_SWIZZLE_NONE);
        encode_2d(fn, &m.wkv[2], d_in[7], 16, DM, 8, 256, CU_TENSOR_MAP_SWIZZLE_NONE);
        encode_2d(fn, &m.wkv[3], d_in[8], 16, DM, 8, 256, CU_TENSOR_MAP_SWIZZLE_NONE);
        encode_2d(fn, &m.o, po, DM, 2 * SEQ, 64, 64);
        encode_2d(fn, &m.wo[0], d_in[4], DM, DM, 64, 64);
        encode_2d(fn, &m.wo[1], d_in[9], DM, DM, 64, 64);
        cudaFuncSetAttribute(fused_kernel, cudaFuncAttributeMaxDynamicSharedMemorySize, SMEM_TOTAL);
        int dev = 0, sms = 0;
        cudaGetDevice(&dev);
        cudaDeviceGetAttribute(&sms, cudaDevAttrMultiProcessorCount, dev);
        grid = sms >= 132 ? 132 : 128;
        for (int i = 0; i < 11; i++) cached[i] = d_in[i];
        attr_done = true;
    }
    cudaLaunchAttribute at[1];
    at[0].id = cudaLaunchAttributeCooperative;
    at[0].val.cooperative = 1;
    cudaLaunchConfig_t cfg = {};
    cfg.stream = cudaStreamPerThread;
    cfg.attrs = at;
    cfg.numAttrs = 1;
    cfg.gridDim = dim3(grid);
    cfg.blockDim = dim3(512);
    cfg.dynamicSmemBytes = SMEM_TOTAL;
    cudaLaunchKernelEx(&cfg, fused_kernel, m, (const bf16*)d_in[0], (const bf16*)d_in[10], (const bf16*)d_in[1], (const bf16*)d_in[6],
                       (const bf16*)d_in[4], (const bf16*)d_in[9], (bf16*)d_out);
}
```
